```python
import torch

def _softmax(x, axis=-1):
    return torch.softmax(x, dim=axis)
def _gelu(x):
    return torch.nn.functional.gelu(x, approximate="tanh")
def _silu(x):
    return torch.nn.functional.silu(x)
def _sigmoid(x):
    return torch.sigmoid(x)
def _layernorm(x, axis=-1, eps=1e-5):
    m = x.mean(dim=axis, keepdim=True)
    v = x.var(dim=axis, keepdim=True, unbiased=False)
    return (x - m) / torch.sqrt(v + eps)
def _scatter_add(tgt, idx, src, axis=0):
    return tgt.clone().index_add_(axis, idx, src)
def _segment_sum(src, seg, n):
    out = torch.zeros((n,) + src.shape[1:], dtype=src.dtype)
    return out.index_add_(0, seg, src)
def _pad(x, pw):
    flat = tuple(v for pair in reversed(pw) for v in pair)
    return torch.nn.functional.pad(x, flat)

kernel_name = 'standalone__ssm_conv_s4__prompt'

def setup_inputs():

    _w = (lambda a: (lambda t: t.to(torch.bfloat16) if t.is_floating_point() else t)(torch.as_tensor(a)))
    B, L, D, N = 1, 2048, 576, 128
    A_re = -(lambda _x: torch.exp(torch.as_tensor(_x)))((lambda *s: torch.randn(*s, dtype=torch.bfloat16) * 3.2)(D, N))
    A_im = torch.pi * (lambda *s: torch.randn(*s, dtype=torch.bfloat16) * 0.05)(D, N)
    B_re = (lambda *s: torch.randn(*s, dtype=torch.bfloat16) * 0.1)(D, N)
    B_im = (lambda *s: torch.randn(*s, dtype=torch.bfloat16) * 0.1)(D, N)
    C_re = (lambda *s: torch.randn(*s, dtype=torch.bfloat16) * 0.1)(D, N)
    C_im = (lambda *s: torch.randn(*s, dtype=torch.bfloat16) * 0.1)(D, N)
    log_dt = (lambda *s: torch.randn(*s, dtype=torch.bfloat16) * 0.05)(D) * 0.5 - 4.0
    Dskip = (lambda *s: torch.randn(*s, dtype=torch.bfloat16) * 0.05)(D)
    return {
        "u": _w((lambda *s: torch.randn(*s, dtype=torch.bfloat16) * 0.05)(B, L, D)),
        "A_re": _w(A_re),
        "A_im": _w(A_im),
        "B_re": _w(B_re),
        "B_im": _w(B_im),
        "C_re": _w(C_re),
        "C_im": _w(C_im),
        "log_dt": _w(log_dt),
        "Dskip": _w(Dskip),
    }

def reference(u, A_re, A_im, B_re, B_im, C_re, C_im, log_dt, Dskip):
    Bsz, L, D = u.shape
    dt = torch.exp(log_dt)[:, None]
    A = A_re + 1j * A_im
    Bc = B_re + 1j * B_im
    Cc = C_re + 1j * C_im
    logdA = dt * A
    dB = dt * Bc
    l = (lambda x, dt: x.to(dt))(torch.arange(L), A_re.dtype)
    P = torch.exp(logdA[:, :, None] * l[None, None, :])
    K = torch.einsum("dn,dnl,dn->dl", Cc, P, dB).real
    L2 = 2 * L
    Kp = _pad(K, ((0, 0), (0, L)))
    up = (lambda x, *d: x.permute(*d))(u, 0, 2, 1)
    up = _pad(up, ((0, 0), (0, 0), (0, L)))
    Kf = (lambda x, axes=(-2,-1): torch.fft.rfft2(x.float(), dim=axes))(Kp[:, None, :], axes=(-2, -1))
    Uf = (lambda x, axes=(-2,-1): torch.fft.rfft2(x.float(), dim=axes))(up[:, :, None, :], axes=(-2, -1))
    Yf = Uf * Kf[None, :, :, :]
    y = (lambda x, s, axes=(-2,-1): torch.fft.irfft2(x, s=s, dim=axes).to(torch.bfloat16))(Yf, (1, L2), axes=(-2, -1))[:, :, 0, :L]
    y = (lambda x, *d: x.permute(*d))(y, 0, 2, 1) + u * Dskip[None, None, :]
    return y
```

```cpp
#include <cuda_runtime.h>
#include <cuda_bf16.h>
#include <stdint.h>

#define LSEQ 2048
#define DCH 576
#define NST 128

__device__ float g_K[DCH * LSEQ];

__device__ __forceinline__ float bf16r(float x) { return __bfloat162float(__float2bfloat16_rn(x)); }

__global__ void kgen_kernel(const __nv_bfloat16* __restrict__ Are, const __nv_bfloat16* __restrict__ Aim,
                            const __nv_bfloat16* __restrict__ Bre, const __nv_bfloat16* __restrict__ Bim,
                            const __nv_bfloat16* __restrict__ Cre, const __nv_bfloat16* __restrict__ Cim,
                            const __nv_bfloat16* __restrict__ logdt) {
    __shared__ float slr[NST], sli[NST], scr[NST], sci[NST];
    int d = blockIdx.x;
    float dt = bf16r(expf(__bfloat162float(logdt[d])));
    if (threadIdx.x < NST) {
        int n = threadIdx.x;
        float ar = __bfloat162float(Are[d * NST + n]), ai = __bfloat162float(Aim[d * NST + n]);
        float br = dt * __bfloat162float(Bre[d * NST + n]), bi = dt * __bfloat162float(Bim[d * NST + n]);
        float cr = __bfloat162float(Cre[d * NST + n]), ci = __bfloat162float(Cim[d * NST + n]);
        slr[n] = dt * ar; sli[n] = dt * ai;
        scr[n] = cr * br - ci * bi; sci[n] = cr * bi + ci * br;
    }
    __syncthreads();
    for (int l = threadIdx.x; l < LSEQ; l += blockDim.x) {
        float lf = bf16r((float)l);
        float acc = 0.f;
        for (int n = 0; n < NST; n++) {
            float m = expf(slr[n] * lf);
            float s, c;
            sincosf(sli[n] * lf, &s, &c);
            acc += m * (scr[n] * c - sci[n] * s);
        }
        g_K[d * LSEQ + l] = acc;
    }
}

__global__ void conv_kernel(const __nv_bfloat16* __restrict__ u, const __nv_bfloat16* __restrict__ Dsk,
                            __nv_bfloat16* __restrict__ out) {
    __shared__ float su[LSEQ];
    __shared__ float sk[LSEQ];
    int d = blockIdx.x;
    for (int l = threadIdx.x; l < LSEQ; l += blockDim.x) {
        su[l] = __bfloat162float(u[l * DCH + d]);
        sk[l] = g_K[d * LSEQ + l];
    }
    __syncthreads();
    float dsk = __bfloat162float(Dsk[d]);
    for (int t = threadIdx.x; t < LSEQ; t += blockDim.x) {
        float acc = 0.f;
        for (int l = 0; l <= t; l++) acc += sk[l] * su[t - l];
        float y = bf16r(acc) + bf16r(su[t] * dsk);
        out[t * DCH + d] = __float2bfloat16_rn(y);
    }
}

extern "C" void kernel_launch(void* const* d_in, const int* in_sizes, int n_in, void* d_out, int out_size) {
    const __nv_bfloat16* u = (const __nv_bfloat16*)d_in[0];
    kgen_kernel<<<DCH, 256, 0, cudaStreamPerThread>>>((const __nv_bfloat16*)d_in[1], (const __nv_bfloat16*)d_in[2],
                              (const __nv_bfloat16*)d_in[3], (const __nv_bfloat16*)d_in[4],
                              (const __nv_bfloat16*)d_in[5], (const __nv_bfloat16*)d_in[6],
                              (const __nv_bfloat16*)d_in[7]);
    conv_kernel<<<DCH, 256, 0, cudaStreamPerThread>>>(u, (const __nv_bfloat16*)d_in[8], (__nv_bfloat16*)d_out);
}
```

```cpp
#include <cuda_runtime.h>
#include <cuda_bf16.h>
#include <cuda_fp16.h>
#include <stdint.h>

namespace {

constexpr int LSEQ = 2048, DCH = 576, NST = 128;
constexpr int OFF_UP = 0;
constexpr int OFF_XS = 5120;
constexpr int OFF_U2 = 7680;
constexpr int OFF_U4 = 11008;
constexpr int OFF_KP = 13312;
constexpr int OFF_PT = 15744;
constexpr int OFF_TA1 = 19072;
constexpr int OFF_TB = 19328;
constexpr int OFF_TA2 = 19584;
constexpr int OFF_E = 19920;
constexpr int OFF_R1 = 20192;
constexpr int OFF_KX = 20720;
constexpr int OFF_TQ = 21120;
constexpr int CH_BYTES = 34176;
constexpr int OFF_SC0 = 13312, OFF_SC1 = 24448;
constexpr int OFF_EX0 = 21120, OFF_EX1 = 24448;
constexpr int OFF_DS = 5 * CH_BYTES;
constexpr int OFF_QX = OFF_DS + 21504;
constexpr int OFF_BAR = OFF_QX + 4096;
constexpr int SMEM_BYTES = OFF_BAR + 128;

__device__ __forceinline__ uint32_t pack_bf16(float lo, float hi) {
    uint32_t r; asm("cvt.rn.bf16x2.f32 %0, %1, %2;" : "=r"(r) : "f"(hi), "f"(lo)); return r;
}
__device__ __forceinline__ uint32_t pack_f16(float lo, float hi) {
    uint32_t r; asm("cvt.rn.f16x2.f32 %0, %1, %2;" : "=r"(r) : "f"(hi), "f"(lo)); return r;
}
__device__ __forceinline__ void mma_bf16(float (&d)[4], uint32_t a0, uint32_t a1, uint32_t a2, uint32_t a3, uint32_t b0, uint32_t b1, const float (&c)[4]) {
    asm volatile("mma.sync.aligned.m16n8k16.row.col.f32.bf16.bf16.f32 {%0,%1,%2,%3},{%4,%5,%6,%7},{%8,%9},{%10,%11,%12,%13};"
        : "=f"(d[0]), "=f"(d[1]), "=f"(d[2]), "=f"(d[3])
        : "r"(a0), "r"(a1), "r"(a2), "r"(a3), "r"(b0), "r"(b1), "f"(c[0]), "f"(c[1]), "f"(c[2]), "f"(c[3]));
}
__device__ __forceinline__ void mma_bf16_acc(float (&d)[4], uint32_t a0, uint32_t a1, uint32_t a2, uint32_t a3, uint32_t b0, uint32_t b1) {
    asm volatile("mma.sync.aligned.m16n8k16.row.col.f32.bf16.bf16.f32 {%0,%1,%2,%3},{%4,%5,%6,%7},{%8,%9},{%0,%1,%2,%3};"
        : "+f"(d[0]), "+f"(d[1]), "+f"(d[2]), "+f"(d[3])
        : "r"(a0), "r"(a1), "r"(a2), "r"(a3), "r"(b0), "r"(b1));
}
__device__ __forceinline__ void mma_bf16_zero(float (&d)[4], uint32_t a0, uint32_t a1, uint32_t a2, uint32_t a3, uint32_t b0, uint32_t b1) {
    asm volatile("mma.sync.aligned.m16n8k16.row.col.f32.bf16.bf16.f32 {%0,%1,%2,%3},{%4,%5,%6,%7},{%8,%9},{%10,%10,%10,%10};"
        : "=f"(d[0]), "=f"(d[1]), "=f"(d[2]), "=f"(d[3])
        : "r"(a0), "r"(a1), "r"(a2), "r"(a3), "r"(b0), "r"(b1), "f"(0.f));
}
__device__ __forceinline__ void mma_f16_acc(float (&d)[4], uint32_t a0, uint32_t a1, uint32_t a2, uint32_t a3, uint32_t b0, uint32_t b1) {
    asm volatile("mma.sync.aligned.m16n8k16.row.col.f32.f16.f16.f32 {%0,%1,%2,%3},{%4,%5,%6,%7},{%8,%9},{%0,%1,%2,%3};"
        : "+f"(d[0]), "+f"(d[1]), "+f"(d[2]), "+f"(d[3])
        : "r"(a0), "r"(a1), "r"(a2), "r"(a3), "r"(b0), "r"(b1));
}
__device__ __forceinline__ void ldsm4(uint32_t& r0, uint32_t& r1, uint32_t& r2, uint32_t& r3, uint32_t addr) {
    asm volatile("ldmatrix.sync.aligned.m8n8.x4.shared.b16 {%0,%1,%2,%3}, [%4];" : "=r"(r0), "=r"(r1), "=r"(r2), "=r"(r3) : "r"(addr));
}
__device__ __forceinline__ void ldsm2(uint32_t& r0, uint32_t& r1, uint32_t addr) {
    asm volatile("ldmatrix.sync.aligned.m8n8.x2.shared.b16 {%0,%1}, [%2];" : "=r"(r0), "=r"(r1) : "r"(addr));
}
__device__ __forceinline__ void ldsm4t(uint32_t& r0, uint32_t& r1, uint32_t& r2, uint32_t& r3, uint32_t addr) {
    asm volatile("ldmatrix.sync.aligned.m8n8.x4.trans.shared.b16 {%0,%1,%2,%3}, [%4];" : "=r"(r0), "=r"(r1), "=r"(r2), "=r"(r3) : "r"(addr));
}
__device__ __forceinline__ uint32_t movm(uint32_t a) {
    uint32_t r; asm volatile("movmatrix.sync.aligned.m8n8.trans.b16 %0, %1;" : "=r"(r) : "r"(a)); return r;
}
__device__ __forceinline__ uint32_t lds32(uint32_t a) { uint32_t v; asm volatile("ld.shared.b32 %0, [%1];" : "=r"(v) : "r"(a)); return v; }
__device__ __forceinline__ uint32_t lds16(uint32_t a) { uint16_t v; asm volatile("ld.shared.u16 %0, [%1];" : "=h"(v) : "r"(a)); return v; }
__device__ __forceinline__ uint2 lds64(uint32_t a) { uint2 v; asm volatile("ld.shared.v2.b32 {%0,%1}, [%2];" : "=r"(v.x), "=r"(v.y) : "r"(a)); return v; }
__device__ __forceinline__ uint4 lds128(uint32_t a) { uint4 v; asm volatile("ld.shared.v4.b32 {%0,%1,%2,%3}, [%4];" : "=r"(v.x), "=r"(v.y), "=r"(v.z), "=r"(v.w) : "r"(a)); return v; }
__device__ __forceinline__ void sts16(uint32_t a, uint32_t v) { asm volatile("st.shared.u16 [%0], %1;" :: "r"(a), "h"((uint16_t)v) : "memory"); }
__device__ __forceinline__ void sts32(uint32_t a, uint32_t v) { asm volatile("st.shared.b32 [%0], %1;" :: "r"(a), "r"(v) : "memory"); }
__device__ __forceinline__ void sts64(uint32_t a, uint32_t x, uint32_t y) { asm volatile("st.shared.v2.b32 [%0], {%1,%2};" :: "r"(a), "r"(x), "r"(y) : "memory"); }
__device__ __forceinline__ void sts128(uint32_t a, uint32_t x, uint32_t y, uint32_t z, uint32_t w) { asm volatile("st.shared.v4.b32 [%0], {%1,%2,%3,%4};" :: "r"(a), "r"(x), "r"(y), "r"(z), "r"(w) : "memory"); }
__device__ __forceinline__ void sts128f(uint32_t a, const float (&v)[4]) { asm volatile("st.shared.v4.f32 [%0], {%1,%2,%3,%4};" :: "r"(a), "f"(v[0]), "f"(v[1]), "f"(v[2]), "f"(v[3]) : "memory"); }
__device__ __forceinline__ float4 lds128f(uint32_t a) { float4 v; asm volatile("ld.shared.v4.f32 {%0,%1,%2,%3}, [%4];" : "=f"(v.x), "=f"(v.y), "=f"(v.z), "=f"(v.w) : "r"(a)); return v; }
__device__ __forceinline__ uint32_t mapa(uint32_t a, uint32_t rank) { uint32_t r; asm("mapa.shared::cluster.u32 %0, %1, %2;" : "=r"(r) : "r"(a), "r"(rank)); return r; }
__device__ __forceinline__ void st_async4(uint32_t addr, uint32_t mbar, uint32_t x, uint32_t y, uint32_t z, uint32_t w) {
    asm volatile("st.async.weak.shared::cluster.mbarrier::complete_tx::bytes.v4.b32 [%0], {%1,%2,%3,%4}, [%5];"
        :: "r"(addr), "r"(x), "r"(y), "r"(z), "r"(w), "r"(mbar) : "memory");
}
__device__ __forceinline__ void mbar_init(uint32_t a, uint32_t cnt) { asm volatile("mbarrier.init.shared::cta.b64 [%0], %1;" :: "r"(a), "r"(cnt) : "memory"); }
__device__ __forceinline__ void mbar_expect(uint32_t a, uint32_t bytes) { asm volatile("mbarrier.arrive.expect_tx.shared::cta.b64 _, [%0], %1;" :: "r"(a), "r"(bytes) : "memory"); }
__device__ __forceinline__ void mbar_arrive(uint32_t a) { asm volatile("mbarrier.arrive.shared::cta.b64 _, [%0];" :: "r"(a) : "memory"); }
__device__ __forceinline__ void mbar_wait(uint32_t a) {
    uint32_t ok; int it = 0;
    do {
        asm volatile("{\n.reg .pred p;\nmbarrier.try_wait.parity.acquire.cluster.shared::cta.b64 p, [%1], 0;\nselp.u32 %0, 1, 0, p;\n}" : "=r"(ok) : "r"(a) : "memory");
    } while (!ok && ++it < (1 << 22));
}
__device__ __forceinline__ void bar_sync(int id, int n) { asm volatile("bar.sync %0, %1;" :: "r"(id), "r"(n) : "memory"); }
__device__ __forceinline__ void bar_arrive(int id, int n) { asm volatile("bar.arrive %0, %1;" :: "r"(id), "r"(n) : "memory"); }
__device__ __forceinline__ uint32_t hmul2(uint32_t a, uint32_t b) { uint32_t r; asm("mul.rn.f16x2 %0, %1, %2;" : "=r"(r) : "r"(a), "r"(b)); return r; }
__device__ __forceinline__ uint32_t hfma2(uint32_t a, uint32_t b, uint32_t c) { uint32_t r; asm("fma.rn.f16x2 %0, %1, %2, %3;" : "=r"(r) : "r"(a), "r"(b), "r"(c)); return r; }
__device__ __forceinline__ uint32_t hneg2(uint32_t a) { uint32_t r; asm("neg.f16x2 %0, %1;" : "=r"(r) : "r"(a)); return r; }
__device__ __forceinline__ uint32_t bsub2(uint32_t a, uint32_t b) { uint32_t r; asm("sub.rn.bf16x2 %0, %1, %2;" : "=r"(r) : "r"(a), "r"(b)); return r; }
__device__ __forceinline__ uint32_t badd2(uint32_t a, uint32_t b) { uint32_t r; asm("add.rn.bf16x2 %0, %1, %2;" : "=r"(r) : "r"(a), "r"(b)); return r; }
__device__ __forceinline__ float ex2f(float x) { float r; asm("ex2.approx.ftz.f32 %0, %1;" : "=f"(r) : "f"(x)); return r; }
__device__ __forceinline__ float sinf_a(float x) { float r; asm("sin.approx.ftz.f32 %0, %1;" : "=f"(r) : "f"(x)); return r; }
__device__ __forceinline__ float cosf_a(float x) { float r; asm("cos.approx.ftz.f32 %0, %1;" : "=f"(r) : "f"(x)); return r; }
__device__ __forceinline__ float bflo(uint32_t w) { return __uint_as_float(w << 16); }
__device__ __forceinline__ float bfhi(uint32_t w) { return __uint_as_float(w & 0xffff0000u); }

struct cf { float r, i; };
struct ch2 { uint32_t r, i; };
__device__ __forceinline__ cf csq(cf a) { cf o; o.r = fmaf(a.r, a.r, -a.i * a.i); o.i = 2.f * a.r * a.i; return o; }
__device__ __forceinline__ ch2 cmul(ch2 a, ch2 b) {
    ch2 o; o.r = hfma2(a.r, b.r, hneg2(hmul2(a.i, b.i))); o.i = hfma2(a.r, b.i, hmul2(a.i, b.r)); return o;
}
__device__ __forceinline__ ch2 cpack(cf a, cf b) { ch2 o; o.r = pack_f16(a.r, b.r); o.i = pack_f16(a.i, b.i); return o; }
__device__ __forceinline__ ch2 cpackc(cf a, cf b) { ch2 o; o.r = pack_f16(a.r, b.r); o.i = pack_f16(-a.i, -b.i); return o; }
__device__ __forceinline__ cf cexp_p(float lr2, float lt) {
    float m = ex2f(lr2);
    float th = lt - rintf(lt);
    th *= 6.283185307179586f;
    cf o; o.r = m * cosf_a(th); o.i = m * sinf_a(th); return o;
}

struct KParams { uint32_t ar, ai, br, bi, cr, ci; };

__device__ __forceinline__ float kgen_pass(const KParams& p, float dt, uint32_t sc, int lane, float (&acc)[2][3][4]) {
    const int g = lane >> 2, q = lane & 3;
    float inv_scale;
    {
        const float L2E = 1.4426950408889634f, I2P = 0.15915494309189535f;
        float lra = dt * bflo(p.ar), lrb = dt * bfhi(p.ar), lia = dt * bflo(p.ai), lib = dt * bfhi(p.ai);
        float bra = dt * bflo(p.br), brb = dt * bfhi(p.br), bia = dt * bflo(p.bi), bib = dt * bfhi(p.bi);
        float cra = bflo(p.cr), crb = bfhi(p.cr), cia = bflo(p.ci), cib = bfhi(p.ci);
        cf cba, cbb;
        cba.r = cra * bra - cia * bia; cba.i = cra * bia + cia * bra;
        cbb.r = crb * brb - cib * bib; cbb.i = crb * bib + cib * brb;
        float mx = fmaxf(fmaxf(fabsf(cba.r), fabsf(cba.i)), fmaxf(fabsf(cbb.r), fabsf(cbb.i)));
        uint32_t mb = __reduce_max_sync(0xffffffffu, __float_as_uint(mx));
        uint32_t e = mb >> 23; e = min(max(e, 1u), 253u);
        float scale = __uint_as_float((254u - e) << 23);
        inv_scale = __uint_as_float(e << 23);
        cba.r *= scale; cba.i *= scale; cbb.r *= scale; cbb.i *= scale;
        float ea = lra * L2E, eb = lrb * L2E, ta = lia * I2P, tb = lib * I2P;
        cf a1 = cexp_p(ea, ta), b1 = cexp_p(eb, tb);
        cf a32 = cexp_p(ea * 32.f, ta * 32.f), b32 = cexp_p(eb * 32.f, tb * 32.f);
        cf a2 = csq(a1), b2 = csq(b1), a4 = csq(a2), b4 = csq(b2), a8 = csq(a4), b8 = csq(b4), a16 = csq(a8), b16 = csq(b8);
        cf a64 = csq(a32), b64 = csq(b32), a128 = csq(a64), b128 = csq(b64), a256 = csq(a128), b256 = csq(b128);
        cf a512 = csq(a256), b512 = csq(b256), a1024 = csq(a512), b1024 = csq(b512);
        ch2 F[8];
        ch2 z8 = cpack(a8, b8), z16 = cpack(a16, b16), z32 = cpack(a32, b32), z64 = cpack(a64, b64), z128 = cpack(a128, b128);
        F[0].r = 0x3c003c00u; F[0].i = 0u;
        F[1] = z8; F[2] = z16; F[3] = cmul(z8, z16); F[4] = z32; F[5] = cmul(z32, z8); F[6] = cmul(z32, z16); F[7] = cmul(z32, F[3]);
        const uint32_t ta_addr = sc + lane * 16;
#pragma unroll
        for (int j = 0; j < 8; j++) {
            ch2 W = (j == 0) ? z64 : cmul(F[j], z64);
            sts128(ta_addr + j * 576, F[j].r, W.r, F[j].i, W.i);
        }
        ch2 x1 = cpackc(a1, b1), x2 = cpackc(a2, b2), x4 = cpackc(a4, b4), x256 = cpackc(a256, b256), x512 = cpackc(a512, b512), x1024 = cpackc(a1024, b1024);
        ch2 P[8], R[8];
        P[0] = cpackc(cba, cbb);
        P[1] = cmul(P[0], x1); P[2] = cmul(P[0], x2); P[3] = cmul(P[1], x2);
        P[4] = cmul(P[0], x4); P[5] = cmul(P[1], x4); P[6] = cmul(P[2], x4); P[7] = cmul(P[3], x4);
        R[0] = cmul(P[0], x256); R[1] = cmul(R[0], x2); R[2] = cmul(R[0], x4); R[3] = cmul(R[1], x4);
        R[4] = cmul(R[0], x512);
        R[5] = cmul(P[4], x512);
        R[6] = cmul(R[0], x1024);
        R[7] = cmul(R[4], x1024);
        const uint32_t tb_addr = sc + 4608 + lane * 16;
#pragma unroll
        for (int j = 0; j < 8; j++) sts128(tb_addr + j * 576, P[j].r, P[j].i, R[j].r, R[j].i);
        sts128(sc + 9216 + lane * 16, z128.r, z128.i, x256.r, x256.i);
    }
    __syncwarp();
    const uint32_t fa = sc + g * 576 + q * 16, fc = sc + 9216 + q * 16;
#pragma unroll
    for (int k = 0; k < 8; k++) {
        uint4 A = lds128(fa + k * 64);
        uint4 B = lds128(fa + 4608 + k * 64);
        uint4 C = lds128(fc + k * 64);
        uint32_t a10 = hfma2(A.x, C.x, hneg2(hmul2(A.z, C.y)));
        uint32_t a11 = hfma2(A.y, C.x, hneg2(hmul2(A.w, C.y)));
        uint32_t a12 = hfma2(A.x, C.y, hmul2(A.z, C.x));
        uint32_t a13 = hfma2(A.y, C.y, hmul2(A.w, C.x));
        uint32_t b20 = hfma2(B.z, C.z, hneg2(hmul2(B.w, C.w)));
        uint32_t b21 = hfma2(B.z, C.w, hmul2(B.w, C.z));
        mma_f16_acc(acc[0][0], A.x, A.y, A.z, A.w, B.x, B.y);
        mma_f16_acc(acc[0][1], A.x, A.y, A.z, A.w, B.z, B.w);
        mma_f16_acc(acc[0][2], A.x, A.y, A.z, A.w, b20, b21);
        mma_f16_acc(acc[1][0], a10, a11, a12, a13, B.x, B.y);
        mma_f16_acc(acc[1][1], a10, a11, a12, a13, B.z, B.w);
        mma_f16_acc(acc[1][2], a10, a11, a12, a13, b20, b21);
    }
    return inv_scale;
}

__device__ __forceinline__ void kgen_epi0(uint32_t chb, int lane, float (&k0)[2][4], float dsk) {
    const int g = lane >> 2, q = lane & 3;
    if (lane == 0) k0[0][0] += dsk;
    uint32_t w[4], v[4];
    w[0] = pack_bf16(k0[0][1], k0[0][0]);
    w[1] = pack_bf16(k0[0][3], k0[0][2]);
    w[2] = pack_bf16(k0[1][1], k0[1][0]);
    w[3] = pack_bf16(k0[1][3], k0[1][2]);
#pragma unroll
    for (int s = 0; s < 4; s++) v[s] = __shfl_sync(0xffffffffu, w[s], (lane + 31) & 31);
    const uint32_t kp = chb + OFF_KP + 32 * 4 + (8 * g + 2 * q) * 4;
#pragma unroll
    for (int s = 0; s < 4; s++) {
        uint32_t x = (lane == 0) ? (s == 0 ? 0u : v[s - 1]) : v[s];
        uint32_t ev = __byte_perm(w[s], x, 0x5432);
        sts64(kp + s * 256, ev, w[s]);
    }
    sts32(chb + OFF_KP + lane * 4, 0u);
    sts64(chb + OFF_KP + (32 + 512) * 4 + lane * 8, 0u, 0u);
}

__device__ __forceinline__ void kgen_epi1(uint32_t chb, int lane, float (&k1)[2][2][4], float k255) {
    const int g = lane >> 2, q = lane & 3;
    {
        sts32(chb + OFF_TA1 + (lane & 15) * 4 + (lane >> 4) * 192, 0u);
        sts32(chb + OFF_TB + (lane & 15) * 4 + (lane >> 4) * 192, 0u);
        if (lane < 16) sts32(chb + OFF_TA2 + lane * 4, 0u);
        else if (lane < 20) sts32(chb + OFF_TA2 + 320 + (lane - 16) * 4, 0u);
    }
    __syncwarp();
    float k512 = __shfl_sync(0xffffffffu, k1[0][1][0], 0);
    if (lane == 29) k1[1][0][3] -= k512;
    uint32_t dummy = chb + OFF_KX;
    uint32_t a10, a11, a20, a21;
    if (q == 2) { a10 = chb + OFF_TA1 + (96 - 32) * 2; a11 = chb + OFF_TB + (64 - 32) * 2; a20 = chb + OFF_TA2 + (128 - 96) * 2; a21 = chb + OFF_TB + (96 - 32) * 2; }
    else if (q == 3) { a10 = chb + OFF_TA2 + (160 - 96) * 2; a11 = chb + OFF_TA2 + (224 - 96) * 2; a20 = chb + OFF_TA2 + (192 - 96) * 2; a21 = dummy; }
    else if (q == 0) { a10 = chb + OFF_E; a11 = chb + OFF_E + 2; a20 = chb + OFF_TA1 + (64 - 32) * 2; a21 = dummy; }
    else { a10 = chb + OFF_E + 4; a11 = chb + OFF_E + 6; a20 = dummy; a21 = dummy; }
    const int st1 = (q < 2) ? 8 : 2;
#pragma unroll
    for (int mt = 0; mt < 2; mt++)
#pragma unroll
        for (int h = 0; h < 2; h++) {
            int j = 16 * mt + 8 * h + g;
            uint32_t p1 = pack_bf16(k1[mt][0][2 * h], k1[mt][0][2 * h + 1]);
            uint32_t p2 = pack_bf16(k1[mt][1][2 * h], k1[mt][1][2 * h + 1]);
            sts16(a10 + j * st1, p1 & 0xffffu); sts16(a11 + j * st1, p1 >> 16);
            sts16(a20 + j * 2, p2 & 0xffffu); sts16(a21 + j * 2, p2 >> 16);
            if (mt == 0 && h == 0 && lane == 3) sts16(chb + OFF_TA2 + (256 - 96) * 2, p2 >> 16);
        }
    if (lane == 0) sts64(chb + OFF_E + 32 * 8, 0u, 0u);
    __syncwarp();
    uint2 e = lds64(chb + OFF_E + lane * 8);
    uint32_t en = lds32(chb + OFF_E + lane * 8 + 8);
    uint32_t c00 = __byte_perm(e.x, 0, 0x1010);
    uint32_t w0 = c00;
    if (lane == 0) w0 = __byte_perm(e.x, pack_bf16(k255, 0.f), 0x5410);
    uint32_t w2 = __byte_perm(e.x, 0, 0x1032);
    uint32_t w3 = __byte_perm(e.y, e.x, 0x7610);
    uint32_t w4 = __byte_perm(e.y, 0, 0x1010);
    uint32_t w6 = __byte_perm(e.y, 0, 0x1032);
    uint32_t w7 = __byte_perm(en, e.y, 0x7610);
    const uint32_t kp = chb + OFF_KP + (32 + 256 + 8 * lane) * 4;
    sts128(kp, w0, c00, w2, w3);
    sts128(kp + 16, w4, w4, w6, w7);
}

__device__ __forceinline__ void build_tq(uint32_t chb, int lane, int rd) {
    int i = 2 * rd + (lane >> 4), dp = lane & 15;
    uint32_t a = chb + OFF_KP + (32 + 32 * i + dp - 6) * 4;
    uint32_t m24 = lds32(a - 96), m16 = lds32(a - 64), m8 = lds32(a - 32), c0 = lds32(a), p8 = lds32(a + 32), p16 = lds32(a + 64), p24 = lds32(a + 96);
    uint32_t t = chb + OFF_TQ + i * 256 + dp * 16;
    if (i < 17) {
        sts128(t, c0, p8, m8, c0);
        uint32_t x0 = bsub2(m16, c0);
        sts128(t + 4352, x0, bsub2(m8, p8), bsub2(m24, m8), x0);
        uint32_t y0 = bsub2(p16, c0);
        sts128(t + 8704, y0, bsub2(p24, p8), bsub2(p8, m8), y0);
    }
}

__device__ __forceinline__ void build_pt(uint32_t chb, int lane, int part, int nparts) {
    for (int r = part; r < 8; r += nparts) {
        int T = r >> 1, par = r & 1, y = 8 + lane, x = 2 * y + par;
        uint32_t base = chb + ((T & 1) ? OFF_TB : OFF_TA1) + (2 * x + (T >> 1) - 32) * 2;
        uint32_t v0 = lds16(base), v1 = (x >= 17 + 0) ? lds16(base - 4) : 0u, v2 = (x >= 18) ? lds16(base - 8) : 0u, v3 = (x >= 19) ? lds16(base - 12) : 0u;
        sts64(chb + OFF_PT + T * 512 + par * 256 + lane * 8, v0 | (v2 << 16), v1 | (v3 << 16));
    }
    for (int r = part; r < 6; r += nparts) {
        int idx = r * 32 + lane;
        int T = idx / 80, rem = idx % 80, par = rem / 40, yy = rem % 40;
        int x = 2 * (24 + yy) + par;
        if (idx < 160) {
            uint32_t base = chb + OFF_TA2 + (2 * x + T - 96) * 2;
            uint32_t v0 = lds16(base), v1 = (x >= 49) ? lds16(base - 4) : 0u, v2 = (x >= 50) ? lds16(base - 8) : 0u, v3 = (x >= 51) ? lds16(base - 12) : 0u;
            sts64(chb + OFF_PT + 2048 + T * 640 + par * 320 + yy * 8, v0 | (v2 << 16), v1 | (v3 << 16));
        }
    }
    for (int r = (part + 2) % nparts; r < 5; r += nparts) {
        int ap = r * 32 + lane;
        if (ap < 132) {
            uint32_t t1 = (ap >= 32 && ap < 64) ? lds16(chb + OFF_TA1 + (2 * ap - 32) * 2) : 0u;
            uint32_t t5 = (ap >= 64 && ap <= 128) ? lds16(chb + OFF_TA2 + (2 * ap - 96) * 2) : 0u;
            sts32(chb + OFF_R1 + ap * 4, t1 | (t5 << 16));
        }
    }
    if (part == nparts - 1) {
        uint32_t c = lds16(chb + OFF_TA2 + (128 - 96) * 2) ^ 0x8000u;
#pragma unroll
        for (int h = 0; h < 2; h++) {
            int l = 992 + 32 * h + lane;
            uint32_t w = (l == 1020) ? c : (l == 1021) ? (c | (c << 16)) : (l == 1022) ? (c << 16) : 0u;
            sts32(chb + OFF_KX + (32 * h + lane) * 4, w);
        }
    }
}

__device__ __forceinline__ void build_u(uint32_t chb, int lane, int half) {
    int al = 32 * half + lane;
    uint32_t a = chb + OFF_UP + (16 + al) * 16;
    uint4 pv = lds128(a + 3 * 1280 - 16);
    uint4 c0 = lds128(a), c1 = lds128(a + 1280), c2 = lds128(a + 2560), c3 = lds128(a + 3840);
    uint32_t xs = chb + OFF_XS + (16 + al) * 16;
    sts128(xs, badd2(c0.x, c2.x), badd2(c0.y, c2.y), badd2(c0.z, c2.z), badd2(c0.w, c2.w));
    sts128(xs + 1280, badd2(c1.x, c3.x), badd2(c1.y, c3.y), badd2(c1.z, c3.z), badd2(c1.w, c3.w));
    if (al <= 50) {
        uint32_t u2 = chb + OFF_U2 + (al + 1) * 16;
        sts128(u2, pv.y, pv.z, pv.w, c0.x);
        sts128(u2 + 832, c0.y, c0.z, c0.w, c1.x);
        sts128(u2 + 1664, c1.y, c1.z, c1.w, c2.x);
        sts128(u2 + 2496, c2.y, c2.z, c2.w, c3.x);
    }
    if (al <= 34) {
        uint32_t u4 = chb + OFF_U4 + (al + 1) * 16;
        sts128(u4, pv.z, pv.w, c0.x, c0.y);
        sts128(u4 + 576, c0.z, c0.w, c1.x, c1.y);
        sts128(u4 + 1152, c1.z, c1.w, c2.x, c2.y);
        sts128(u4 + 1728, c2.z, c2.w, c3.x, c3.y);
    }
}

template <int TBL>
__device__ __forceinline__ void g01_pass(uint32_t lb, uint32_t lb1, uint32_t ta, bool first_half, float (&acc)[4][4], const float (&cin)[4][4]) {
    uint32_t B[41][2];
#pragma unroll
    for (int i = 0; i <= 16; i++) {
        if (i < 8) {
            ldsm4(B[16 - i][0], B[16 - i][1], B[24 - i][0], B[24 - i][1], lb - i * 16);
            ldsm4(B[32 - i][0], B[32 - i][1], B[40 - i][0], B[40 - i][1], lb + 256 - i * 16);
        } else if ((i & 1) == 0) {
            if (i < 16) ldsm4(B[15 - i][0], B[15 - i][1], B[16 - i][0], B[16 - i][1], lb1 - (i + 1) * 16);
            else ldsm2(B[0][0], B[0][1], lb1 - 256);
        }
        uint4 A = lds128(ta + TBL * 4352 + i * 256);
#pragma unroll
        for (int tp = 0; tp < 4; tp++) {
            if (tp == 0 && i > 7 && first_half) continue;
            if (tp == 1 && i > 15 && first_half) continue;
            const int bi = 16 + 8 * tp - i;
            if (i == 0) {
                if (TBL == 0) mma_bf16_zero(acc[tp], A.x, A.y, A.z, A.w, B[bi][0], B[bi][1]);
                else mma_bf16(acc[tp], A.x, A.y, A.z, A.w, B[bi][0], B[bi][1], cin[tp]);
            } else mma_bf16_acc(acc[tp], A.x, A.y, A.z, A.w, B[bi][0], B[bi][1]);
        }
    }
}

__device__ __forceinline__ void g01(uint32_t chb, int lane, int tau0, float (&ae)[4][4], float (&ao)[4][4]) {
    const int g = lane >> 2, q = lane & 3, m = lane >> 3, rho = lane & 7;
    const uint32_t off8 = (m & 1) * 1280 + (16 + 8 * tau0 + rho + (m >> 1) * 8) * 16;
    const uint32_t off1 = (m & 1) * 1280 + (16 + 8 * tau0 + rho + (m >> 1)) * 16;
    const uint32_t ta = chb + OFF_TQ + (g - 2 * q + 6) * 16;
    const bool fh = (tau0 == 0);
    g01_pass<0>(chb + OFF_XS + off8, chb + OFF_XS + off1, ta, fh, ao, ao);
    g01_pass<1>(chb + OFF_UP + 2560 + off8, chb + OFF_UP + 2560 + off1, ta, fh, ae, ao);
    g01_pass<2>(chb + OFF_UP + off8, chb + OFF_UP + off1, ta, fh, ao, ao);
}

__device__ __forceinline__ void etiles(uint32_t l1, uint32_t l2, uint32_t l3, const uint4& band, uint32_t (&EA)[5], uint32_t (&EB)[5]) {
    uint32_t m0, m1, m2, m3, n0, n1, n2, n3, o0, o1;
    ldsm4(m0, m1, m2, m3, l1);
    ldsm4(n0, n1, n2, n3, l2);
    ldsm2(o0, o1, l3);
    float e[4];
    mma_bf16_zero(e, band.x, band.y, band.z, band.w, m0, m1); EA[0] = pack_bf16(e[0], e[1]); EB[0] = pack_bf16(e[2], e[3]);
    mma_bf16_zero(e, band.x, band.y, band.z, band.w, n0, n1); EA[1] = pack_bf16(e[0], e[1]); EB[1] = pack_bf16(e[2], e[3]);
    mma_bf16_zero(e, band.x, band.y, band.z, band.w, m2, m3); EA[2] = pack_bf16(e[0], e[1]); EB[2] = pack_bf16(e[2], e[3]);
    mma_bf16_zero(e, band.x, band.y, band.z, band.w, n2, n3); EA[3] = pack_bf16(e[0], e[1]); EB[3] = pack_bf16(e[2], e[3]);
    mma_bf16_zero(e, band.x, band.y, band.z, band.w, o0, o1); EA[4] = pack_bf16(e[0], e[1]); EB[4] = pack_bf16(e[2], e[3]);
}

template <int TAU0>
__device__ __forceinline__ void g23(uint32_t chb, int lane, const uint4& band2, const uint4& band4, float (&ae)[4][4], float (&ao)[4][4]) {
    const int g = lane >> 2, q = lane & 3, m = lane >> 3, rho = lane & 7;
    const int c1 = m - 1, c2 = m, c3 = 3 + (m & 1);
    const uint32_t u2l1 = chb + OFF_U2 + (c1 & 3) * 832 + (rho + 1 + (c1 >> 2)) * 16;
    const uint32_t u2l2 = chb + OFF_U2 + (c2 & 3) * 832 + (rho + 1) * 16;
    const uint32_t u2l3 = chb + OFF_U2 + (c3 & 3) * 832 + (rho + 1 + (c3 >> 2)) * 16;
    const uint32_t u4l1 = chb + OFF_U4 + (c1 & 3) * 576 + (rho + 1 + (c1 >> 2)) * 16;
    const uint32_t u4l2 = chb + OFF_U4 + (c2 & 3) * 576 + (rho + 1) * 16;
    const uint32_t u4l3 = chb + OFF_U4 + (c3 & 3) * 576 + (rho + 1 + (c3 >> 2)) * 16;
    uint32_t r1a = 0;
    {
        uint2 Bf[4][2][3];
        const uint32_t pt = chb + OFF_PT + (g - 2 * q - 8) * 8;
#pragma unroll
        for (int T = 0; T < 4; T++)
#pragma unroll
            for (int par = 0; par < 2; par++)
#pragma unroll
                for (int d = 0; d < 3; d++)
                    if (TAU0 == 4 || d < 2) Bf[T][par][d] = lds64(pt + T * 512 + par * 256 + (d + 2) * 64);
        constexpr int KMAX = (TAU0 == 4) ? 6 : 2;
#pragma unroll
        for (int k = 0; k < KMAX; k++) {
            uint32_t EA[5], EB[5];
            etiles(u2l1 + k * 128, u2l2 + k * 128, u2l3 + k * 128, band2, EA, EB);
            if (k == 0) r1a = EA[0];
#pragma unroll
            for (int d = 0; d < 3; d++) {
                const int tau = k + d + 2;
                if (tau < TAU0 || tau >= TAU0 + 4) continue;
                const int tp = tau - TAU0;
                mma_bf16_acc(ae[tp], EA[1], EA[2], EA[3], EA[4], Bf[0][0][d].x, Bf[0][0][d].y);
                mma_bf16_acc(ao[tp], EA[1], EA[2], EA[3], EA[4], Bf[0][1][d].x, Bf[0][1][d].y);
                mma_bf16_acc(ae[tp], EB[1], EB[2], EB[3], EB[4], Bf[1][0][d].x, Bf[1][0][d].y);
                mma_bf16_acc(ao[tp], EB[1], EB[2], EB[3], EB[4], Bf[1][1][d].x, Bf[1][1][d].y);
                mma_bf16_acc(ae[tp], EA[0], EA[1], EA[2], EA[3], Bf[2][0][d].x, Bf[2][0][d].y);
                mma_bf16_acc(ao[tp], EA[0], EA[1], EA[2], EA[3], Bf[2][1][d].x, Bf[2][1][d].y);
                mma_bf16_acc(ae[tp], EB[0], EB[1], EB[2], EB[3], Bf[3][0][d].x, Bf[3][0][d].y);
                mma_bf16_acc(ao[tp], EB[0], EB[1], EB[2], EB[3], Bf[3][1][d].x, Bf[3][1][d].y);
            }
        }
    }
    uint32_t r1b = 0;
    if (TAU0 == 4) {
        uint2 Bf[2][2][4];
        const uint32_t pt = chb + OFF_PT + 2048 + (g - 2 * q - 24) * 8;
#pragma unroll
        for (int T = 0; T < 2; T++)
#pragma unroll
            for (int par = 0; par < 2; par++)
#pragma unroll
                for (int d = 0; d < 4; d++) Bf[T][par][d] = lds64(pt + T * 640 + par * 320 + (d + 4) * 64);
#pragma unroll
        for (int k = 0; k < 4; k++) {
            uint32_t EA[5], EB[5];
            etiles(u4l1 + k * 128, u4l2 + k * 128, u4l3 + k * 128, band4, EA, EB);
            if (k == 0) r1b = EA[0];
#pragma unroll
            for (int d = 0; d < 4; d++) {
                const int tau = k + d + 4;
                if (tau >= 8) continue;
                const int tp = tau - 4;
                mma_bf16_acc(ae[tp], EA[1], EA[2], EA[3], EA[4], Bf[0][0][d].x, Bf[0][0][d].y);
                mma_bf16_acc(ao[tp], EA[1], EA[2], EA[3], EA[4], Bf[0][1][d].x, Bf[0][1][d].y);
                mma_bf16_acc(ae[tp], EB[0], EB[1], EB[2], EB[3], Bf[1][0][d].x, Bf[1][0][d].y);
                mma_bf16_acc(ao[tp], EB[0], EB[1], EB[2], EB[3], Bf[1][1][d].x, Bf[1][1][d].y);
            }
        }
    } else {
        uint32_t m0, m1;
        ldsm2(m0, m1, u4l1);
        float e[4];
        mma_bf16_zero(e, band4.x, band4.y, band4.z, band4.w, m0, m1);
        r1b = pack_bf16(e[0], e[1]);
    }
    {
        uint32_t a1 = (q == 0) ? __byte_perm(r1a, r1b, 0x5410) : 0u;
        const uint32_t rb = (q == 0) ? (chb + OFF_R1 + (2 * g + 1) * 4) : (chb + OFF_R1);
        const uint32_t mul = (q == 0) ? 1u : 0u;
#pragma unroll
        for (int tp = 0; tp < 4; tp++) {
            const int tau = TAU0 + tp;
            if (tau < 1) continue;
            uint32_t be = lds32(rb + mul * (16 * tau * 4)), bo = lds32(rb + mul * (16 * tau * 4 + 4));
            if (tau >= 2) mma_bf16_acc(ae[tp], 0u, a1, 0u, 0u, be, 0u);
            mma_bf16_acc(ao[tp], 0u, a1, 0u, 0u, bo, 0u);
        }
    }
    {
        const uint32_t kx = chb + OFF_KX + (g - 2 * q) * 4;
        uint32_t f64a0 = lds32(kx + 32 * 4), f64a1 = lds32(kx + 40 * 4), f64a2 = lds32(kx + 24 * 4);
        uint32_t f63a0 = lds32(kx + 16 * 4), f63a1 = lds32(kx + 24 * 4), f63a2 = lds32(kx + 8 * 4);
        const uint32_t l0 = chb + OFF_UP + m * 1280 + (16 + rho) * 16;
#pragma unroll
        for (int tp = 0; tp < 4; tp++) {
            const int tau = TAU0 + tp;
            if (tau < 3) continue;
            const int beta = 8 * tau - 32;
            uint32_t e0, e1, o0, o1, f0, f1;
            ldsm2(f0, f1, l0 + (beta + 1) * 16);
            mma_bf16_acc(ao[tp], f63a0, f63a1, f63a2, f63a0, f0, f1);
            if (tau >= 4) {
                ldsm4(e0, e1, o0, o1, l0 + beta * 16);
                mma_bf16_acc(ae[tp], f64a0, f64a1, f64a2, f64a0, e0, e1);
                mma_bf16_acc(ae[tp], f63a0, f63a1, f63a2, f63a0, o0, o1);
                mma_bf16_acc(ao[tp], f64a0, f64a1, f64a2, f64a0, o0, o1);
            }
        }
    }
}

__device__ __forceinline__ void send_out(uint32_t smem0, int chl  , int lane, int tau0, const float (&ae)[4][4], const float (&ao)[4][4]) {
    const uint32_t la = smem0 + OFF_DS + chl * 528 + 32 * (chl >> 3) + lane * 16;
    const uint32_t lbar = smem0 + OFF_BAR + 40;
#pragma unroll
    for (int tp = 0; tp < 4; tp++) {
        uint32_t ra = mapa(la, tau0 + tp), rbar = mapa(lbar, tau0 + tp);
        st_async4(ra, rbar, pack_bf16(ae[tp][0], ae[tp][1]), pack_bf16(ae[tp][2], ae[tp][3]), pack_bf16(ao[tp][0], ao[tp][1]), pack_bf16(ao[tp][2], ao[tp][3]));
    }
}

__constant__ uint32_t c_dummy[1];

__global__ void __cluster_dims__(8, 1, 1) __launch_bounds__(384, 1)
ssm_kernel(const __nv_bfloat16* __restrict__ u, const __nv_bfloat16* __restrict__ Are, const __nv_bfloat16* __restrict__ Aim,
           const __nv_bfloat16* __restrict__ Bre, const __nv_bfloat16* __restrict__ Bim, const __nv_bfloat16* __restrict__ Cre,
           const __nv_bfloat16* __restrict__ Cim, const __nv_bfloat16* __restrict__ logdt, const __nv_bfloat16* __restrict__ Dsk,
           __nv_bfloat16* __restrict__ out) {
    extern __shared__ __align__(1024) uint8_t smem[];
    const uint32_t sm0 = (uint32_t)__cvta_generic_to_shared(smem);
    const int tid = threadIdx.x, warp = tid >> 5, lane = tid & 31, g = lane >> 2, q = lane & 3;
    const int rank = blockIdx.x & 7, cl = blockIdx.x >> 3;
    const int chbase = 40 * cl;
    const bool isQ = warp >= 8;
    const int slot = isQ ? 4 : (warp & 3);
    const int half = (warp >> 2) & 1;
    const int qi = warp - 8;
    const uint32_t chb = sm0 + slot * CH_BYTES;
    const uint32_t inbar = sm0 + OFF_BAR;
    int ch = chbase + 5 * rank + slot; if (ch >= DCH) ch = DCH - 1;

    KParams kp0, kp1;
    uint4 ul[4][4];
    float dt = 0.f, dsk = 0.f;
    const bool doK = !isQ || qi == 3;
    if (doK) {
        const int s0 = (isQ ? 0 : 64 * half) + 2 * lane;
        const size_t o = (size_t)ch * NST + s0;
        kp0.ar = *(const uint32_t*)(Are + o); kp0.ai = *(const uint32_t*)(Aim + o); kp0.br = *(const uint32_t*)(Bre + o);
        kp0.bi = *(const uint32_t*)(Bim + o); kp0.cr = *(const uint32_t*)(Cre + o); kp0.ci = *(const uint32_t*)(Cim + o);
        if (isQ) {
            kp1.ar = *(const uint32_t*)(Are + o + 64); kp1.ai = *(const uint32_t*)(Aim + o + 64); kp1.br = *(const uint32_t*)(Bre + o + 64);
            kp1.bi = *(const uint32_t*)(Bim + o + 64); kp1.cr = *(const uint32_t*)(Cre + o + 64); kp1.ci = *(const uint32_t*)(Cim + o + 64);
        }
        dt = __bfloat162float(logdt[ch]); dsk = __bfloat162float(Dsk[ch]);
    } else {
#pragma unroll
        for (int k = 0; k < 3; k++) {
            const int task = 3 * qi + k;
            const bool valid = task < 8 && (chbase + 8 * q) < DCH;
#pragma unroll
            for (int r = 0; r < 4; r++) {
                const int row = 256 * rank + 32 * task + 8 * (g >> 1) + 2 * r + (g & 1);
                ul[k][r] = valid ? __ldg((const uint4*)(u + (size_t)row * DCH + chbase + 8 * q)) : make_uint4(0, 0, 0, 0);
            }
        }
        {
            const bool valid = qi < 2 && (chbase + 32) < DCH;
#pragma unroll
            for (int r = 0; r < 4; r++) {
                const int row = 256 * rank + 128 * qi + 8 * (4 * (g >> 1) + q) + 2 * r + (g & 1);
                ul[3][r] = valid ? __ldg((const uint4*)(u + (size_t)row * DCH + chbase + 32)) : make_uint4(0, 0, 0, 0);
            }
        }
    }
    if (tid == 0) {
#pragma unroll
        for (int s = 0; s < 5; s++) { mbar_init(inbar + 8 * s, 1); }
        mbar_init(inbar + 40, 1);
        mbar_init(inbar + 48, 3);
        asm volatile("fence.mbarrier_init.release.cluster;" ::: "memory");
#pragma unroll
        for (int s = 0; s < 5; s++) mbar_expect(inbar + 8 * s, 4096);
        mbar_expect(inbar + 40, 40 * 512);
    }
    asm volatile("barrier.cluster.arrive.release.aligned;" ::: "memory");

    uint4 band2, band4;
    {
        auto inr = [](int k, int lo, int hi) { return (k >= lo && k <= hi) ? 0x3f80u : 0u; };
        const int k0 = 2 * q;
        band2.x = inr(k0, g + 4, g + 8) | (inr(k0 + 1, g + 4, g + 8) << 16);
        band2.y = inr(k0, g + 1, g + 3) | (inr(k0 + 1, g + 1, g + 3) << 16);
        band2.z = inr(k0 + 8, g + 4, g + 8) | (inr(k0 + 9, g + 4, g + 8) << 16);
        band2.w = inr(k0 + 8, g + 1, g + 3) | (inr(k0 + 9, g + 1, g + 3) << 16);
        band4.x = inr(k0, g, g + 8) | (inr(k0 + 1, g, g + 8) << 16);
        band4.y = inr(k0, g + 1, g + 7) | (inr(k0 + 1, g + 1, g + 7) << 16);
        band4.z = inr(k0 + 8, g, g + 8) | (inr(k0 + 9, g, g + 8) << 16);
        band4.w = inr(k0 + 8, g + 1, g + 7) | (inr(k0 + 9, g + 1, g + 7) << 16);
    }

    float ae[4][4], ao[4][4];

    if (doK) {
        dt = __bfloat162float(__float2bfloat16_rn(expf(dt)));
        float acc[2][3][4];
#pragma unroll
        for (int a = 0; a < 2; a++)
#pragma unroll
            for (int b = 0; b < 3; b++)
#pragma unroll
                for (int c = 0; c < 4; c++) acc[a][b][c] = 0.f;
        if (!isQ) {
            const uint32_t sc = chb + (half ? OFF_SC1 : OFF_SC0);
            float is = kgen_pass(kp0, dt, sc, lane, acc);
            __syncwarp();
            if (half == 0) {
#pragma unroll
                for (int mt = 0; mt < 2; mt++)
#pragma unroll
                    for (int nt = 1; nt < 3; nt++) {
                        float v[4] = {acc[mt][nt][0] * is, acc[mt][nt][1] * is, acc[mt][nt][2] * is, acc[mt][nt][3] * is};
                        sts128f(chb + OFF_EX0 + (mt * 2 + nt - 1) * 512 + lane * 16, v);
                    }
                if (lane == 31) sts32(chb + OFF_EX0 + 2048, __float_as_uint(acc[1][0][3] * is));
            } else {
#pragma unroll
                for (int mt = 0; mt < 2; mt++) {
                    float v[4] = {acc[mt][0][0] * is, acc[mt][0][1] * is, acc[mt][0][2] * is, acc[mt][0][3] * is};
                    sts128f(chb + OFF_EX1 + mt * 512 + lane * 16, v);
                }
            }
            bar_sync(1 + slot, 64);
            if (half == 0) {
                float k0[2][4];
#pragma unroll
                for (int mt = 0; mt < 2; mt++) {
                    float4 o = lds128f(chb + OFF_EX1 + mt * 512 + lane * 16);
                    k0[mt][0] = fmaf(acc[mt][0][0], is, o.x); k0[mt][1] = fmaf(acc[mt][0][1], is, o.y);
                    k0[mt][2] = fmaf(acc[mt][0][2], is, o.z); k0[mt][3] = fmaf(acc[mt][0][3], is, o.w);
                }
                kgen_epi0(chb, lane, k0, dsk);
            } else {
                float k1[2][2][4];
#pragma unroll
                for (int mt = 0; mt < 2; mt++)
#pragma unroll
                    for (int nt = 1; nt < 3; nt++) {
                        float4 o = lds128f(chb + OFF_EX0 + (mt * 2 + nt - 1) * 512 + lane * 16);
                        k1[mt][nt - 1][0] = fmaf(acc[mt][nt][0], is, o.x); k1[mt][nt - 1][1] = fmaf(acc[mt][nt][1], is, o.y);
                        k1[mt][nt - 1][2] = fmaf(acc[mt][nt][2], is, o.z); k1[mt][nt - 1][3] = fmaf(acc[mt][nt][3], is, o.w);
                    }
                float own255 = __shfl_sync(0xffffffffu, acc[1][0][3], 31) * is;
                float k255 = own255 + __uint_as_float(lds32(chb + OFF_EX0 + 2048));
                kgen_epi1(chb, lane, k1, k255);
            }
            bar_sync(1 + slot, 64);
            if (half == 0) {
#pragma unroll 1
                for (int rd = 0; rd < 6; rd++) build_tq(chb, lane, rd);
            } else {
#pragma unroll 1
                for (int rd = 6; rd < 9; rd++) build_tq(chb, lane, rd);
                build_pt(chb, lane, 0, 1);
            }
            bar_sync(1 + slot, 64);
        } else {
            const uint32_t sc = chb + OFF_SC1;
            float acc2[2][3][4];
#pragma unroll
            for (int a = 0; a < 2; a++)
#pragma unroll
                for (int b = 0; b < 3; b++)
#pragma unroll
                    for (int c = 0; c < 4; c++) acc2[a][b][c] = 0.f;
            float is0 = kgen_pass(kp0, dt, sc, lane, acc);
            __syncwarp();
            float is1 = kgen_pass(kp1, dt, sc, lane, acc2);
            __syncwarp();
            float k0[2][4], k1[2][2][4];
#pragma unroll
            for (int mt = 0; mt < 2; mt++)
#pragma unroll
                for (int c = 0; c < 4; c++) {
                    k0[mt][c] = acc[mt][0][c] * is0 + acc2[mt][0][c] * is1;
                    k1[mt][0][c] = acc[mt][1][c] * is0 + acc2[mt][1][c] * is1;
                    k1[mt][1][c] = acc[mt][2][c] * is0 + acc2[mt][2][c] * is1;
                }
            float k255 = __shfl_sync(0xffffffffu, k0[1][3], 31);
            kgen_epi0(chb, lane, k0, dsk);
            kgen_epi1(chb, lane, k1, k255);
        }
    }
    asm volatile("barrier.cluster.wait.acquire.aligned;" ::: "memory");
    if (!doK) {
#pragma unroll
        for (int k = 0; k < 3; k++) {
            const int task = 3 * qi + k;
            if (task < 8) {
#pragma unroll
                for (int i = 0; i < 4; i++) {
                    uint32_t w0, w1, w2, w3;
                    w0 = movm(i == 0 ? ul[k][0].x : i == 1 ? ul[k][0].y : i == 2 ? ul[k][0].z : ul[k][0].w);
                    w1 = movm(i == 0 ? ul[k][1].x : i == 1 ? ul[k][1].y : i == 2 ? ul[k][1].z : ul[k][1].w);
                    w2 = movm(i == 0 ? ul[k][2].x : i == 1 ? ul[k][2].y : i == 2 ? ul[k][2].z : ul[k][2].w);
                    w3 = movm(i == 0 ? ul[k][3].x : i == 1 ? ul[k][3].y : i == 2 ? ul[k][3].z : ul[k][3].w);
                    const int c = 8 * (g >> 1) + 2 * i + (g & 1);
                    const int dr = c / 5, ds = c % 5;
                    uint32_t la = sm0 + ds * CH_BYTES + OFF_UP + q * 1280 + (16 + 8 * rank + task) * 16;
                    st_async4(mapa(la, dr), mapa(inbar + 8 * ds, dr), w0, w1, w2, w3);
                }
            }
        }
        if (qi < 2) {
#pragma unroll
            for (int i = 0; i < 4; i++) {
                uint32_t w0, w1, w2, w3;
                w0 = movm(i == 0 ? ul[3][0].x : i == 1 ? ul[3][0].y : i == 2 ? ul[3][0].z : ul[3][0].w);
                w1 = movm(i == 0 ? ul[3][1].x : i == 1 ? ul[3][1].y : i == 2 ? ul[3][1].z : ul[3][1].w);
                w2 = movm(i == 0 ? ul[3][2].x : i == 1 ? ul[3][2].y : i == 2 ? ul[3][2].z : ul[3][2].w);
                w3 = movm(i == 0 ? ul[3][3].x : i == 1 ? ul[3][3].y : i == 2 ? ul[3][3].z : ul[3][3].w);
                const int c = 32 + 2 * i + (g & 1);
                const int dr = c / 5, ds = c % 5;
                uint32_t la = sm0 + ds * CH_BYTES + OFF_UP + (g >> 1) * 1280 + (16 + 8 * rank + 4 * qi + q) * 16;
                st_async4(mapa(la, dr), mapa(inbar + 8 * ds, dr), w0, w1, w2, w3);
            }
        }
#pragma unroll 1
        for (int s = qi; s < 5; s += 3) {
            const uint32_t cb2 = sm0 + s * CH_BYTES;
#pragma unroll
            for (int r = 0; r < 3; r++) {
                int idx = r * 32 + lane;
                sts128(cb2 + (idx >> 4) * 1280 + (idx & 15) * 16, 0, 0, 0, 0);
            }
            if (lane < 4) sts128(cb2 + OFF_U2 + lane * 832, 0, 0, 0, 0);
            else if (lane < 8) sts128(cb2 + OFF_U4 + (lane - 4) * 576, 0, 0, 0, 0);
        }
        bar_sync(7, 96);
#pragma unroll 1
        for (int job = qi; job < 10; job += 3) {
            const int s = job >> 1;
            mbar_wait(inbar + 8 * s);
            build_u(sm0 + s * CH_BYTES, lane, job & 1);
        }
        __syncwarp();
        if (lane == 0) mbar_arrive(inbar + 48);
    }
    if (isQ) {
        bar_sync(5, 128);
        for (int rd = qi; rd < 9; rd += 4) build_tq(chb, lane, rd);
        build_pt(chb, lane, qi, 4);
        bar_sync(5, 128);
    }
    mbar_wait(inbar + 48);
    const int chl = 5 * rank + slot;
    if (!isQ) {
        g01(chb, lane, 4 * half, ae, ao);
        if (half == 0) g23<0>(chb, lane, band2, band4, ae, ao);
        else g23<4>(chb, lane, band2, band4, ae, ao);
        send_out(sm0, chl, lane, 4 * half, ae, ao);
    } else if (qi == 0) {
        g01(chb, lane, 0, ae, ao);
        g23<0>(chb, lane, band2, band4, ae, ao);
        send_out(sm0, chl, lane, 0, ae, ao);
    } else if (qi == 1) {
        g01(chb, lane, 4, ae, ao);
        bar_sync(6, 64);
#pragma unroll
        for (int tp = 0; tp < 4; tp++) {
            float4 a = lds128f(sm0 + OFF_QX + (2 * tp) * 512 + lane * 16), b = lds128f(sm0 + OFF_QX + (2 * tp + 1) * 512 + lane * 16);
            ae[tp][0] += a.x; ae[tp][1] += a.y; ae[tp][2] += a.z; ae[tp][3] += a.w;
            ao[tp][0] += b.x; ao[tp][1] += b.y; ao[tp][2] += b.z; ao[tp][3] += b.w;
        }
        send_out(sm0, chl, lane, 4, ae, ao);
    } else if (qi == 2) {
#pragma unroll
        for (int tp = 0; tp < 4; tp++)
#pragma unroll
            for (int c = 0; c < 4; c++) { ae[tp][c] = 0.f; ao[tp][c] = 0.f; }
        g23<4>(chb, lane, band2, band4, ae, ao);
#pragma unroll
        for (int tp = 0; tp < 4; tp++) {
            sts128f(sm0 + OFF_QX + (2 * tp) * 512 + lane * 16, ae[tp]);
            sts128f(sm0 + OFF_QX + (2 * tp + 1) * 512 + lane * 16, ao[tp]);
        }
        bar_arrive(6, 64);
    }
    mbar_wait(inbar + 40);
    {
        const int m = lane >> 3, rho = lane & 7;
#pragma unroll 1
        for (int job = warp; job < 40; job += 12) {
            uint32_t r0, r1, r2, r3;
            if (job < 32) {
                const int c = 8 * (rho >> 1) + 2 * m + (rho & 1);
                ldsm4t(r0, r1, r2, r3, sm0 + OFF_DS + c * 528 + 32 * (c >> 3) + job * 16);
                const int qs = job & 3, gs = job >> 2;
                const int tl = 64 * qs + gs + 32 * (g & 1) + 8 * ((g >> 1) & 1) + 16 * (g >> 2);
                if (chbase + 8 * q < DCH)
                    *(uint4*)(out + (size_t)(256 * rank + tl) * DCH + chbase + 8 * q) = make_uint4(r0, r1, r2, r3);
            } else {
                const int mm = job - 32;
                const int c = 32 + 2 * m + (rho & 1);
                const int ls = 4 * mm + (rho >> 1);
                ldsm4t(r0, r1, r2, r3, sm0 + OFF_DS + c * 528 + 32 * (c >> 3) + ls * 16);
                const int tl = 64 * q + mm + 32 * (g & 1) + 8 * ((g >> 1) & 1) + 16 * (g >> 2);
                if (chbase + 32 < DCH)
                    *(uint4*)(out + (size_t)(256 * rank + tl) * DCH + chbase + 32) = make_uint4(r0, r1, r2, r3);
            }
        }
    }
}

}

extern "C" void kernel_launch(void* const* d_in, const int* in_sizes, int n_in, void* d_out, int out_size) {
    static bool init = false;
    if (!init) {
        cudaFuncSetAttribute(ssm_kernel, cudaFuncAttributeMaxDynamicSharedMemorySize, SMEM_BYTES);
        init = true;
    }
    ssm_kernel<<<120, 384, SMEM_BYTES, cudaStreamPerThread>>>(
        (const __nv_bfloat16*)d_in[0], (const __nv_bfloat16*)d_in[1], (const __nv_bfloat16*)d_in[2], (const __nv_bfloat16*)d_in[3],
        (const __nv_bfloat16*)d_in[4], (const __nv_bfloat16*)d_in[5], (const __nv_bfloat16*)d_in[6], (const __nv_bfloat16*)d_in[7],
        (const __nv_bfloat16*)d_in[8], (__nv_bfloat16*)d_out);
}
```

```cpp
#include <cuda_runtime.h>
#include <cuda.h>
#include <cuda_bf16.h>
#include <cuda_fp16.h>
#include <stdint.h>

namespace {

constexpr int DCH = 576, NST = 128;
constexpr int RP = 2576;
constexpr int OFF_X = 0;
constexpr int OFF_XS = 10 * RP;
constexpr int OFF_CH = 20 * RP;
constexpr int OFF_U2 = 0;
constexpr int OFF_U4 = OFF_U2 + 3504;
constexpr int U4P = 1376;
constexpr int OFF_CP = OFF_U4 + 2 * U4P;
constexpr int CPS = 416;
constexpr int OFF_KP = OFF_CP + 4 * CPS;
constexpr int KPS = 2432;
constexpr int OFF_MB = OFF_KP + 3 * KPS;
constexpr int MBP = 1072;
constexpr int OFF_SV = OFF_MB + 8 * MBP;
constexpr int OFF_SC0 = OFF_KP + KPS, SCS = 9728;
constexpr int CH_BYTES = OFF_SC0 + 2 * SCS;
static_assert(OFF_SV + 4352 <= CH_BYTES, "layout");
static_assert(CH_BYTES % 16 == 0 && OFF_MB % 16 == 0 && OFF_KP % 16 == 0 && OFF_CP % 16 == 0 && OFF_CH % 16 == 0 && OFF_SV % 16 == 0, "align");
static_assert(4 * CPS + KPS == 4096, "zero region");
constexpr int OFF_DS = (OFF_CH + 5 * CH_BYTES + 127) / 128 * 128;
constexpr int OFF_S = OFF_DS + 21504;
constexpr int OFF_BAR = OFF_S + 4352;
constexpr int SMEM_BYTES = OFF_BAR + 128;

__device__ __forceinline__ uint32_t pack_bf16(float lo, float hi) {
    uint32_t r; asm("cvt.rn.bf16x2.f32 %0, %1, %2;" : "=r"(r) : "f"(hi), "f"(lo)); return r;
}
__device__ __forceinline__ uint32_t pack_f16(float lo, float hi) {
    uint32_t r; asm("cvt.rn.f16x2.f32 %0, %1, %2;" : "=r"(r) : "f"(hi), "f"(lo)); return r;
}
__device__ __forceinline__ void mma_acc(float (&d)[4], uint32_t a0, uint32_t a1, uint32_t a2, uint32_t a3, uint32_t b0, uint32_t b1) {
    asm("mma.sync.aligned.m16n8k16.row.col.f32.bf16.bf16.f32 {%0,%1,%2,%3},{%4,%5,%6,%7},{%8,%9},{%0,%1,%2,%3};"
        : "+f"(d[0]), "+f"(d[1]), "+f"(d[2]), "+f"(d[3])
        : "r"(a0), "r"(a1), "r"(a2), "r"(a3), "r"(b0), "r"(b1));
}
__device__ __forceinline__ void mma_acc(float (&d)[4], const uint4& a, uint32_t b0, uint32_t b1) { mma_acc(d, a.x, a.y, a.z, a.w, b0, b1); }
__device__ __forceinline__ void mma_c(float (&d)[4], const uint4& a, uint32_t b0, uint32_t b1, const float (&c)[4]) {
    asm("mma.sync.aligned.m16n8k16.row.col.f32.bf16.bf16.f32 {%0,%1,%2,%3},{%4,%5,%6,%7},{%8,%9},{%10,%11,%12,%13};"
        : "=f"(d[0]), "=f"(d[1]), "=f"(d[2]), "=f"(d[3])
        : "r"(a.x), "r"(a.y), "r"(a.z), "r"(a.w), "r"(b0), "r"(b1), "f"(c[0]), "f"(c[1]), "f"(c[2]), "f"(c[3]));
}
__device__ __forceinline__ void mma_zero(float (&d)[4], const uint4& a, uint32_t b0, uint32_t b1) {
    asm("mma.sync.aligned.m16n8k16.row.col.f32.bf16.bf16.f32 {%0,%1,%2,%3},{%4,%5,%6,%7},{%8,%9},{%10,%10,%10,%10};"
        : "=f"(d[0]), "=f"(d[1]), "=f"(d[2]), "=f"(d[3])
        : "r"(a.x), "r"(a.y), "r"(a.z), "r"(a.w), "r"(b0), "r"(b1), "f"(0.f));
}
__device__ __forceinline__ void mma_f16_acc(float (&d)[4], uint32_t a0, uint32_t a1, uint32_t a2, uint32_t a3, uint32_t b0, uint32_t b1) {
    asm("mma.sync.aligned.m16n8k16.row.col.f32.f16.f16.f32 {%0,%1,%2,%3},{%4,%5,%6,%7},{%8,%9},{%0,%1,%2,%3};"
        : "+f"(d[0]), "+f"(d[1]), "+f"(d[2]), "+f"(d[3])
        : "r"(a0), "r"(a1), "r"(a2), "r"(a3), "r"(b0), "r"(b1));
}
__device__ __forceinline__ void ldsm4(uint32_t& r0, uint32_t& r1, uint32_t& r2, uint32_t& r3, uint32_t addr) {
    asm volatile("ldmatrix.sync.aligned.m8n8.x4.shared.b16 {%0,%1,%2,%3}, [%4];" : "=r"(r0), "=r"(r1), "=r"(r2), "=r"(r3) : "r"(addr));
}
__device__ __forceinline__ void ldsm4t(uint32_t& r0, uint32_t& r1, uint32_t& r2, uint32_t& r3, uint32_t addr) {
    asm volatile("ldmatrix.sync.aligned.m8n8.x4.trans.shared.b16 {%0,%1,%2,%3}, [%4];" : "=r"(r0), "=r"(r1), "=r"(r2), "=r"(r3) : "r"(addr));
}
__device__ __forceinline__ uint32_t lds32(uint32_t a) { uint32_t v; asm volatile("ld.shared.b32 %0, [%1];" : "=r"(v) : "r"(a)); return v; }
__device__ __forceinline__ uint32_t lds32v(uint32_t a) { uint32_t v; asm volatile("ld.volatile.shared.b32 %0, [%1];" : "=r"(v) : "r"(a)); return v; }
__device__ __forceinline__ uint32_t lds16(uint32_t a) { uint16_t v; asm volatile("ld.shared.u16 %0, [%1];" : "=h"(v) : "r"(a)); return v; }
__device__ __forceinline__ uint2 lds64(uint32_t a) { uint2 v; asm volatile("ld.shared.v2.b32 {%0,%1}, [%2];" : "=r"(v.x), "=r"(v.y) : "r"(a)); return v; }
__device__ __forceinline__ void lds64f(float& x, float& y, uint32_t a) { asm volatile("ld.shared.v2.f32 {%0,%1}, [%2];" : "=f"(x), "=f"(y) : "r"(a)); }
__device__ __forceinline__ uint4 lds128(uint32_t a) { uint4 v; asm volatile("ld.shared.v4.b32 {%0,%1,%2,%3}, [%4];" : "=r"(v.x), "=r"(v.y), "=r"(v.z), "=r"(v.w) : "r"(a)); return v; }
__device__ __forceinline__ float4 lds128f(uint32_t a) { float4 v; asm volatile("ld.shared.v4.f32 {%0,%1,%2,%3}, [%4];" : "=f"(v.x), "=f"(v.y), "=f"(v.z), "=f"(v.w) : "r"(a)); return v; }
__device__ __forceinline__ void sts16(uint32_t a, uint32_t v) { asm volatile("st.shared.u16 [%0], %1;" :: "r"(a), "h"((uint16_t)v) : "memory"); }
__device__ __forceinline__ void sts32(uint32_t a, uint32_t v) { asm volatile("st.shared.b32 [%0], %1;" :: "r"(a), "r"(v) : "memory"); }
__device__ __forceinline__ void sts32f(uint32_t a, float v) { asm volatile("st.shared.f32 [%0], %1;" :: "r"(a), "f"(v) : "memory"); }
__device__ __forceinline__ void sts64(uint32_t a, uint32_t x, uint32_t y) { asm volatile("st.shared.v2.b32 [%0], {%1,%2};" :: "r"(a), "r"(x), "r"(y) : "memory"); }
__device__ __forceinline__ void sts64f(uint32_t a, float x, float y) { asm volatile("st.shared.v2.f32 [%0], {%1,%2};" :: "r"(a), "f"(x), "f"(y) : "memory"); }
__device__ __forceinline__ void sts128(uint32_t a, uint32_t x, uint32_t y, uint32_t z, uint32_t w) { asm volatile("st.shared.v4.b32 [%0], {%1,%2,%3,%4};" :: "r"(a), "r"(x), "r"(y), "r"(z), "r"(w) : "memory"); }
__device__ __forceinline__ void sts128f(uint32_t a, float x, float y, float z, float w) { asm volatile("st.shared.v4.f32 [%0], {%1,%2,%3,%4};" :: "r"(a), "f"(x), "f"(y), "f"(z), "f"(w) : "memory"); }
__device__ __forceinline__ uint32_t mapa(uint32_t a, uint32_t rank) { uint32_t r; asm("mapa.shared::cluster.u32 %0, %1, %2;" : "=r"(r) : "r"(a), "r"(rank)); return r; }
__device__ __forceinline__ void st_async4(uint32_t addr, uint32_t mbar, uint32_t x, uint32_t y, uint32_t z, uint32_t w) {
    asm volatile("st.async.weak.shared::cluster.mbarrier::complete_tx::bytes.v4.b32 [%0], {%1,%2,%3,%4}, [%5];"
        :: "r"(addr), "r"(x), "r"(y), "r"(z), "r"(w), "r"(mbar) : "memory");
}
__device__ __forceinline__ void bulk_s2c(uint32_t dst, uint32_t src, uint32_t bytes, uint32_t mbar) {
    asm volatile("cp.async.bulk.shared::cluster.shared::cta.mbarrier::complete_tx::bytes [%0], [%1], %2, [%3];"
        :: "r"(dst), "r"(src), "r"(bytes), "r"(mbar) : "memory");
}
__device__ __forceinline__ void mbar_init(uint32_t a, uint32_t cnt) { asm volatile("mbarrier.init.shared::cta.b64 [%0], %1;" :: "r"(a), "r"(cnt) : "memory"); }
__device__ __forceinline__ void mbar_expect(uint32_t a, uint32_t bytes) { asm volatile("mbarrier.arrive.expect_tx.shared::cta.b64 _, [%0], %1;" :: "r"(a), "r"(bytes) : "memory"); }
__device__ __forceinline__ void mbar_arrive(uint32_t a) { asm volatile("mbarrier.arrive.shared::cta.b64 _, [%0];" :: "r"(a) : "memory"); }
__device__ __forceinline__ void mbar_wait(uint32_t a) {
    uint32_t ok; int it = 0;
    do {
        asm volatile("{\n.reg .pred p;\nmbarrier.try_wait.parity.acquire.cluster.shared::cta.b64 p, [%1], 0;\nselp.u32 %0, 1, 0, p;\n}" : "=r"(ok) : "r"(a) : "memory");
    } while (!ok && ++it < (1 << 22));
}
__device__ __forceinline__ void bar_sync(int id, int n) { asm volatile("bar.sync %0, %1;" :: "r"(id), "r"(n) : "memory"); }
__device__ __forceinline__ void bar_arrive(int id, int n) { asm volatile("bar.arrive %0, %1;" :: "r"(id), "r"(n) : "memory"); }
__device__ __forceinline__ uint32_t hmul2(uint32_t a, uint32_t b) { uint32_t r; asm("mul.rn.f16x2 %0, %1, %2;" : "=r"(r) : "r"(a), "r"(b)); return r; }
__device__ __forceinline__ uint32_t hfma2(uint32_t a, uint32_t b, uint32_t c) { uint32_t r; asm("fma.rn.f16x2 %0, %1, %2, %3;" : "=r"(r) : "r"(a), "r"(b), "r"(c)); return r; }
__device__ __forceinline__ uint32_t hneg2(uint32_t a) { uint32_t r; asm("neg.f16x2 %0, %1;" : "=r"(r) : "r"(a)); return r; }
__device__ __forceinline__ uint32_t bsub2(uint32_t a, uint32_t b) { uint32_t r; asm("sub.rn.bf16x2 %0, %1, %2;" : "=r"(r) : "r"(a), "r"(b)); return r; }
__device__ __forceinline__ uint32_t badd2(uint32_t a, uint32_t b) { uint32_t r; asm("add.rn.bf16x2 %0, %1, %2;" : "=r"(r) : "r"(a), "r"(b)); return r; }
__device__ __forceinline__ float ex2f(float x) { float r; asm("ex2.approx.ftz.f32 %0, %1;" : "=f"(r) : "f"(x)); return r; }
__device__ __forceinline__ float sinf_a(float x) { float r; asm("sin.approx.ftz.f32 %0, %1;" : "=f"(r) : "f"(x)); return r; }
__device__ __forceinline__ float cosf_a(float x) { float r; asm("cos.approx.ftz.f32 %0, %1;" : "=f"(r) : "f"(x)); return r; }
__device__ __forceinline__ float bflo(uint32_t w) { return __uint_as_float(w << 16); }
__device__ __forceinline__ float bfhi(uint32_t w) { return __uint_as_float(w & 0xffff0000u); }

struct cf { float r, i; };
struct ch2 { uint32_t r, i; };
__device__ __forceinline__ cf csq(cf a) { cf o; o.r = fmaf(a.r, a.r, -a.i * a.i); o.i = (a.r + a.r) * a.i; return o; }
__device__ __forceinline__ ch2 cmul(ch2 a, ch2 b) {
    ch2 o; o.r = hfma2(a.r, b.r, hneg2(hmul2(a.i, b.i))); o.i = hfma2(a.r, b.i, hmul2(a.i, b.r)); return o;
}
__device__ __forceinline__ ch2 cpack(cf a, cf b) { ch2 o; o.r = pack_f16(a.r, b.r); o.i = pack_f16(a.i, b.i); return o; }
__device__ __forceinline__ ch2 cpackc(cf a, cf b) { ch2 o; o.r = pack_f16(a.r, b.r); o.i = pack_f16(-a.i, -b.i); return o; }
__device__ __forceinline__ cf cexp_p(float lr2, float lt) {
    float m = ex2f(lr2);
    float th = lt - rintf(lt);
    th *= 6.283185307179586f;
    cf o; o.r = m * cosf_a(th); o.i = m * sinf_a(th); return o;
}

__device__ __forceinline__ void cp_async16(uint32_t dst, const void* src) {
    asm volatile("cp.async.cg.shared.global [%0], [%1], 16;" :: "r"(dst), "l"(src) : "memory");
}
__device__ __forceinline__ void tma_load4(uint32_t dst, const CUtensorMap* tm, uint32_t mbar, int c0, int c1, int c2, int c3) {
    asm volatile("cp.async.bulk.tensor.4d.shared::cluster.global.tile.mbarrier::complete_tx::bytes [%0], [%1, {%3, %4, %5, %6}], [%2];"
        :: "r"(dst), "l"(tm), "r"(mbar), "r"(c0), "r"(c1), "r"(c2), "r"(c3) : "memory");
}

struct KParams { uint32_t ar, ai, br, bi, cr, ci; };

__device__ __forceinline__ void band_words(uint32_t& w0, uint32_t& w1, int g, int q, int lo, int hi, uint32_t one) {
    const uint32_t b = (((2u << hi) - (1u << lo)) << g) >> (2 * q);
    w0 = ((b & 1u) | ((b & 2u) << 15)) * one;
    w1 = (((b >> 8) & 1u) | ((b & 0x200u) << 7)) * one;
}
#define KUNR 4
constexpr int KUNR_ = KUNR;
#define T12UN 1
constexpr int T12U = T12UN;

__device__ __forceinline__ float kgen_pass(const KParams& p, float dt, uint32_t sc, int lane, float (&acc)[2][3][4]) {
    const int g = lane >> 2, q = lane & 3;
    float inv_scale;
    {
        const float dl = dt * 1.4426950408889634f, di = dt * 0.15915494309189535f;
        float bra = bflo(p.br), brb = bfhi(p.br), bia = bflo(p.bi), bib = bfhi(p.bi);
        float cra = bflo(p.cr), crb = bfhi(p.cr), cia = bflo(p.ci), cib = bfhi(p.ci);
        cf cba, cbb;
        cba.r = cra * bra - cia * bia; cba.i = cra * bia + cia * bra;
        cbb.r = crb * brb - cib * bib; cbb.i = crb * bib + cib * brb;
        float mx = fmaxf(fmaxf(fabsf(cba.r), fabsf(cba.i)), fmaxf(fabsf(cbb.r), fabsf(cbb.i)));
        uint32_t mb = __reduce_max_sync(0xffffffffu, __float_as_uint(mx));
        uint32_t e = mb >> 23; e = min(max(e, 1u), 253u);
        float scale = __uint_as_float((254u - e) << 23);
        inv_scale = __uint_as_float(e << 23) * dt;
        cba.r *= scale; cba.i *= scale; cbb.r *= scale; cbb.i *= scale;
        float ea = bflo(p.ar) * dl, eb = bfhi(p.ar) * dl, ta = bflo(p.ai) * di, tb = bfhi(p.ai) * di;
        cf a1 = cexp_p(ea, ta), b1 = cexp_p(eb, tb);
        cf a32 = cexp_p(ea * 32.f, ta * 32.f), b32 = cexp_p(eb * 32.f, tb * 32.f);
        cf a2 = csq(a1), b2 = csq(b1), a4 = csq(a2), b4 = csq(b2), a8 = csq(a4), b8 = csq(b4), a16 = csq(a8), b16 = csq(b8);
        cf a64 = csq(a32), b64 = csq(b32), a128 = csq(a64), b128 = csq(b64), a256 = csq(a128), b256 = csq(b128);
        cf a512 = csq(a256), b512 = csq(b256), a1024 = csq(a512), b1024 = csq(b512);
        ch2 F[8];
        ch2 z8 = cpack(a8, b8), z16 = cpack(a16, b16), z32 = cpack(a32, b32), z64 = cpack(a64, b64), z128 = cpack(a128, b128);
        F[0].r = 0x3c003c00u; F[0].i = 0u;
        F[1] = z8; F[2] = z16; F[3] = cmul(z8, z16); F[4] = z32; F[5] = cmul(z32, z8); F[6] = cmul(z32, z16); F[7] = cmul(z32, F[3]);
        const uint32_t ta_addr = sc + lane * 16;
#pragma unroll
        for (int j = 0; j < 8; j++) {
            ch2 W = (j == 0) ? z64 : cmul(F[j], z64);
            sts128(ta_addr + j * 576, F[j].r, W.r, F[j].i, W.i);
        }
        ch2 x1 = cpackc(a1, b1), x2 = cpackc(a2, b2), x4 = cpackc(a4, b4), x256 = cpackc(a256, b256), x512 = cpackc(a512, b512), x1024 = cpackc(a1024, b1024);
        ch2 P[8], R[8];
        P[0] = cpackc(cba, cbb);
        P[1] = cmul(P[0], x1); P[2] = cmul(P[0], x2); P[3] = cmul(P[1], x2);
        P[4] = cmul(P[0], x4); P[5] = cmul(P[1], x4); P[6] = cmul(P[2], x4); P[7] = cmul(P[3], x4);
        R[0] = cmul(P[0], x256); R[1] = cmul(R[0], x2); R[2] = cmul(R[0], x4); R[3] = cmul(R[1], x4);
        R[4] = cmul(R[0], x512);
        R[5] = cmul(R[2], x512);
        R[6] = cmul(R[0], x1024);
        R[7] = cmul(R[4], x1024);
        const uint32_t tb_addr = sc + 4608 + lane * 16;
#pragma unroll
        for (int j = 0; j < 8; j++) sts128(tb_addr + j * 576, P[j].r, P[j].i, R[j].r, R[j].i);
        sts128(sc + 9216 + lane * 16, z128.r, z128.i, x256.r, x256.i);
    }
    __syncwarp();
    const uint32_t fa = sc + g * 576 + q * 16, fc = sc + 9216 + q * 16;
#pragma unroll
    for (int a = 0; a < 2; a++)
#pragma unroll
        for (int b = 0; b < 3; b++)
#pragma unroll
            for (int c = 0; c < 4; c++) acc[a][b][c] = 0.f;
    uint4 A = lds128(fa), B = lds128(fa + 4608), C = lds128(fc);
#pragma unroll KUNR_
    for (int k = 0; k < 8; k++) {
        const uint4 An = lds128(fa + k * 64 + 64), Bn = lds128(fa + 4608 + k * 64 + 64), Cn = lds128(fc + k * 64 + 64);
        mma_f16_acc(acc[0][0], A.x, A.y, A.z, A.w, B.x, B.y);
        mma_f16_acc(acc[0][1], A.x, A.y, A.z, A.w, B.z, B.w);
        uint32_t a10 = hfma2(A.x, C.x, hneg2(hmul2(A.z, C.y)));
        uint32_t a11 = hfma2(A.y, C.x, hneg2(hmul2(A.w, C.y)));
        uint32_t a12 = hfma2(A.x, C.y, hmul2(A.z, C.x));
        uint32_t a13 = hfma2(A.y, C.y, hmul2(A.w, C.x));
        uint32_t b20 = hfma2(B.z, C.z, hneg2(hmul2(B.w, C.w)));
        uint32_t b21 = hfma2(B.z, C.w, hmul2(B.w, C.z));
        mma_f16_acc(acc[1][0], a10, a11, a12, a13, B.x, B.y);
        mma_f16_acc(acc[1][1], a10, a11, a12, a13, B.z, B.w);
        mma_f16_acc(acc[0][2], A.x, A.y, A.z, A.w, b20, b21);
        mma_f16_acc(acc[1][2], a10, a11, a12, a13, b20, b21);
        A = An; B = Bn; C = Cn;
    }
    return inv_scale;
}

__device__ __forceinline__ void cp_store(uint32_t a, uint32_t v) { sts16(a, v); sts16(a + 6, v); }

__device__ __forceinline__ void kgen_epi(uint32_t chb, int lane, int h, float (&kf)[3][4], float dsk, float k512) {
    const int g = lane >> 2, q = lane & 3;
    const bool first = (h == 0) && (lane == 0);
    if (first) kf[0][0] += dsk;
    if (h == 1 && lane == 29) kf[1][3] -= k512;
    const uint32_t kp = chb + OFF_KP + (32 + 128 * h + 8 * g + 2 * q) * 4;
#pragma unroll
    for (int rr = 0; rr < 2; rr++) {
        uint32_t w = pack_bf16(kf[0][2 * rr + 1], kf[0][2 * rr]);
        sts32(kp + rr * 256 + 4, w);
        sts16(kp + rr * 256, w >> 16);
        sts16(kp + rr * 256 + 10, w);
    }
    const uint32_t cp = chb + OFF_CP + 64;
    const uint32_t blin = cp + (16 * h + g) * 4;
    const uint32_t bv = cp + (2 + (g & 1)) * CPS + (8 * h + (g >> 1)) * 4;
    uint32_t p1[2], p2[2];
#pragma unroll
    for (int rr = 0; rr < 2; rr++) { p1[rr] = pack_bf16(kf[1][2 * rr], kf[1][2 * rr + 1]); p2[rr] = pack_bf16(kf[2][2 * rr], kf[2][2 * rr + 1]); }
    const bool v = q >= 2;
    {
        const uint32_t a = v ? bv + (q - 2) * 128 : blin + q * CPS;
        cp_store(a, p2[0]);
        cp_store(a + (v ? 16 : 32), p2[1]);
    }
    if (v) {
        const bool w = q == 3;
        const uint32_t ax = w ? bv + 64 : blin + 128, ay = w ? bv + 192 : blin + CPS + 128;
        const int st = w ? 16 : 32;
        cp_store(ax, p1[0]); cp_store(ay, p1[0] >> 16);
        cp_store(ax + st, p1[1]); cp_store(ay + st, p1[1] >> 16);
        if (h == 0 && lane == 3) cp_store(cp + 2 * CPS + 256, p2[0] >> 16);
    } else {
        const uint32_t eb = chb + OFF_KP + (32 + 256 + 128 * h + 8 * g + 4 * q) * 4;
#pragma unroll
        for (int rr = 0; rr < 2; rr++) {
            const uint32_t xx = __byte_perm(p1[rr], 0, 0x1010), yx = __byte_perm(p1[rr], 0, 0x1032);
            const uint32_t e = eb + rr * 256;
            if (rr == 0 && first) { sts16(e, xx); sts32(e + 4, xx); }
            else { sts64(e, xx, xx); sts16(e - 4, xx); }
            sts32(e + 8, yx);
            sts16(e + 14, yx);
        }
    }
}

__device__ __forceinline__ void build_kd(uint32_t chb, int lane, int sel) {
    const uint32_t a = chb + OFF_KP + 64 + lane * 16;
    const uint32_t ao = a + (sel ? 64 : -64), as = a + (1 + sel) * KPS;
    uint4 z[5], o[5];
#pragma unroll
    for (int i = 0; i < 5; i++) if (i < 4 || lane < 8) { z[i] = lds128(a + i * 512); o[i] = lds128(ao + i * 512); }
#pragma unroll
    for (int i = 0; i < 5; i++)
        if (i < 4 || lane < 8) sts128(as + i * 512, bsub2(o[i].x, z[i].x), bsub2(o[i].y, z[i].y), bsub2(o[i].z, z[i].z), bsub2(o[i].w, z[i].w));
}

struct U5 { uint4 pv, c0, c1, c2, c3; };
__device__ __forceinline__ uint4 lds128p(uint32_t a, int pr) {
    uint4 v;
    asm volatile("{\n .reg .pred p;\n setp.ne.s32 p, %5, 0;\n mov.b32 %0, 0;\n mov.b32 %1, 0;\n mov.b32 %2, 0;\n mov.b32 %3, 0;\n @p ld.shared.v4.b32 {%0,%1,%2,%3}, [%4];\n}"
                 : "=r"(v.x), "=r"(v.y), "=r"(v.z), "=r"(v.w) : "r"(a), "r"(pr));
    return v;
}
__device__ __forceinline__ void sts128p(uint32_t a, uint32_t x, uint32_t y, uint32_t z, uint32_t w, int pr) {
    asm volatile("{\n .reg .pred p;\n setp.ne.s32 p, %5, 0;\n @p st.shared.v4.b32 [%0], {%1,%2,%3,%4};\n}" :: "r"(a), "r"(x), "r"(y), "r"(z), "r"(w), "r"(pr) : "memory");
}
__device__ __forceinline__ void load_u(U5& v, uint32_t p, int blk, int li, int pr) {
    v.pv = lds128p(blk ? p - 16 : (li ? p - 1280 + 240 : p - RP + 1280 + 240), pr);
    v.c0 = lds128p(p, pr); v.c1 = lds128p(p + 16, pr); v.c2 = lds128p(p + 32, pr); v.c3 = lds128p(p + 48, pr);
}
__device__ __forceinline__ void store_u(const U5& v, uint32_t p, uint32_t chb, int a, int b, int pr) {
    const uint4 &pv = v.pv, &c0 = v.c0, &c1 = v.c1, &c2 = v.c2, &c3 = v.c3;
    sts128p(p + OFF_XS, badd2(c0.x, c2.x), badd2(c0.y, c2.y), badd2(c0.z, c2.z), badd2(c0.w, c2.w), pr);
    sts128p(p + OFF_XS + 16, badd2(c1.x, c3.x), badd2(c1.y, c3.y), badd2(c1.z, c3.z), badd2(c1.w, c3.w), pr);
    const int p2 = (pr && (a <= 5 || (a == 6 && b == 0))) ? 1 : 0;
    const uint32_t u2 = chb + OFF_U2 + (33 * a + 4 * b + 17) * 16;
    sts128p(u2, pv.y, pv.z, pv.w, c0.x, p2);
    sts128p(u2 + 16, c0.y, c0.z, c0.w, c1.x, p2);
    sts128p(u2 + 32, c1.y, c1.z, c1.w, c2.x, p2);
    sts128p(u2 + 48, c2.y, c2.z, c2.w, c3.x, p2);
    const int p4 = (pr && (a <= 3 || (a == 4 && b == 0))) ? 1 : 0;
    const int p5 = (pr && a <= 3) ? 1 : 0;
    const uint32_t u4 = chb + OFF_U4 + (17 * a + 2 * b + 17) * 16;
    sts128p(u4, pv.z, pv.w, c0.x, c0.y, p4);
    sts128p(u4 + U4P, c0.z, c0.w, c1.x, c1.y, p5);
    sts128p(u4 + 16, c1.z, c1.w, c2.x, c2.y, p5);
    sts128p(u4 + U4P + 16, c2.z, c2.w, c3.x, c3.y, p5);
}

__device__ __forceinline__ uint4 lda(uint32_t a) { uint2 x = lds64(a), y = lds64(a - 32); return make_uint4(x.x, x.y, y.x, y.y); }
__device__ __forceinline__ void ld_q5(uint4 (&Q)[5], uint32_t a) {
#pragma unroll
    for (int i = 0; i < 5; i++) { Q[i].x = lds32v(a + i * 64 + 32); Q[i].y = lds32v(a + i * 64 + 64); Q[i].z = lds32v(a + i * 64); Q[i].w = lds32v(a + i * 64 + 32); }
}

#define TM(i)
#define TMP(i)
#define TMSKIP
__device__ __forceinline__ void tail_terms(uint32_t sm0, int warp, uint32_t chb, int lane, const uint4& band2, const uint4& band4, const uint2& e2m) {
    const int g = lane >> 2, q = lane & 3, m = lane >> 3, rho = lane & 7;
    const int g0 = g & 1, g1 = (g >> 1) & 1, g2 = g >> 2;
#pragma unroll
    for (int it = 0; it < 4; it++) sts128(chb + OFF_MB + (it >> 1) * (4 * MBP) + (it & 1) * 512 + lane * 16, 0, 0, 0, 0);
    __syncwarp();
    {
        const uint32_t cpa = chb + OFF_CP + (8 + g0 + 2 * g2 + 4 * g1 - 2 * q) * 4;
        uint4 Q1[5], Q2[5];
        ld_q5(Q1, cpa); ld_q5(Q2, cpa + CPS);
        int j = -16 + (m & 1) + 8 * (m >> 1) + rho;
        const uint32_t u2 = chb + OFF_U2 + 17 * 16;
        uint32_t ma = chb + OFF_MB + (g2 * MBP + (4 * g0 + q) * 4 + g1 * 2 + 3 * 64 + 4) * 4;
        float o[4][4];
#pragma unroll
        for (int a = 0; a < 4; a++)
#pragma unroll
            for (int c = 0; c < 4; c++) o[a][c] = 0.f;
        uint32_t r0, r1, r2, r3, w10, w11, w20, w21;
        {
            float e0[4], e1[4];
            ldsm4(r0, r1, r2, r3, u2 + (j + (j >> 5)) * 16);
            mma_zero(e0, band2, r0, r1);
            mma_zero(e1, band2, r2, r3);
            j += 16;
            ldsm4(r0, r1, r2, r3, u2 + (j + (j >> 5)) * 16);
            w10 = pack_bf16(e0[0], e0[1]); w20 = pack_bf16(e0[2], e0[3]);
            w11 = pack_bf16(e1[0], e1[1]); w21 = pack_bf16(e1[2], e1[3]);
        }
#define T12_STEP(sg, LIM) { \
            float t[5][4], e0[4], e1[4], f[4]; \
            _Pragma("unroll") \
            for (int i = 0; i < 5; i++) if (i <= (LIM)) { if (i < 4) mma_c(t[i], Q1[i], w10, w11, o[i < 4 ? i : 0]); else mma_zero(t[4], Q1[4], w10, w11); } \
            if ((LIM) >= 1) { mma_zero(e0, band2, r0, r1); mma_zero(e1, band2, r2, r3); } \
            if ((LIM) >= 2) { j += 16; ldsm4(r0, r1, r2, r3, u2 + (j + (j >> 5)) * 16); } \
            if ((LIM) >= 1) mma_c(o[0], Q2[1], w20, w21, t[1]); \
            if ((LIM) >= 2) mma_c(o[1], Q2[2], w20, w21, t[2]); \
            mma_c(f, Q2[0], w20, w21, t[0]); \
            if ((LIM) >= 3) mma_c(o[2], Q2[3], w20, w21, t[3]); \
            if ((LIM) >= 4) mma_c(o[3], Q2[4], w20, w21, t[4]); \
            sts64f(ma, f[0], f[1]); sts64f(ma + 128, f[2], f[3]); \
            ma += ((sg) & 1) ? 256 + 16 : 256; \
            if ((LIM) >= 1) { \
                w10 = pack_bf16(e0[0], e0[1]); w20 = pack_bf16(e0[2], e0[3]); \
                w11 = pack_bf16(e1[0], e1[1]); w21 = pack_bf16(e1[2], e1[3]); \
            } }
#pragma unroll T12U
        for (int sg = 3; sg < 12; sg++) T12_STEP(sg, 4)
        T12_STEP(12, 3) T12_STEP(13, 2) T12_STEP(14, 1) T12_STEP(15, 0)
    }
    __syncwarp();
    TMP(9);
    {
        const uint32_t cpa = chb + OFF_CP + 2 * CPS + (8 + g - 2 * q) * 4;
        uint4 Q5[5], Q6[5], Q6s[5];
        ld_q5(Q5, cpa); ld_q5(Q6, cpa + CPS); ld_q5(Q6s, cpa + CPS - 4);
        uint32_t cE = lds16(chb + OFF_CP + 2 * CPS + 64) ^ 0x8000u;
        cE |= cE << 16;
        const uint32_t bE0 = cE & e2m.x, bE1 = cE & e2m.y;
        const int odd = m >> 1, sec = m & 1;
        uint32_t a_h0 = chb + OFF_U4 + sec * U4P + (8 * odd + rho) * 16;
        uint32_t a_h1 = chb + OFF_U4 + (sec ? 0 : U4P) + (8 * odd + rho + sec + ((odd && sec && rho == 7) ? 1 : 0)) * 16;
        uint32_t mb = chb + OFF_MB + (g0 * MBP + 3 * 132 + g2 * 32 + q * 4 + g1 * 2) * 4;
        float o[4][2][4];
#pragma unroll
        for (int a = 0; a < 4; a++)
#pragma unroll
            for (int b = 0; b < 2; b++)
#pragma unroll
                for (int c = 0; c < 4; c++) o[a][b][c] = 0.f;
        uint32_t S90[2], S91[2], S70[2], S71[2];
        float e2[2][4];
        uint32_t ra[4], rb[4];
        {
            float ea[4], eb[4];
            ldsm4(ra[0], ra[1], ra[2], ra[3], a_h0);
            ldsm4(rb[0], rb[1], rb[2], rb[3], a_h1);
            lds64f(e2[0][0], e2[0][1], mb); lds64f(e2[0][2], e2[0][3], mb + 256);
            lds64f(e2[1][0], e2[1][1], mb + 64); lds64f(e2[1][2], e2[1][3], mb + 320);
            mma_zero(ea, band4, ra[0], ra[1]); mma_zero(eb, band4, ra[2], ra[3]);
            S90[0] = pack_bf16(ea[0], ea[1]); S70[0] = pack_bf16(ea[2], ea[3]); S90[1] = pack_bf16(eb[0], eb[1]); S70[1] = pack_bf16(eb[2], eb[3]);
            mma_zero(ea, band4, rb[0], rb[1]); mma_zero(eb, band4, rb[2], rb[3]);
            S91[0] = pack_bf16(ea[0], ea[1]); S71[0] = pack_bf16(ea[2], ea[3]); S91[1] = pack_bf16(eb[0], eb[1]); S71[1] = pack_bf16(eb[2], eb[3]);
            mma_acc(e2[0], ra[0], ra[2], ra[1], ra[3], bE0, bE1);
            mma_acc(e2[1], rb[0], rb[2], rb[1], rb[3], bE0, bE1);
            a_h0 += 17 * 16; a_h1 += 17 * 16;
            ldsm4(ra[0], ra[1], ra[2], ra[3], a_h0);
            ldsm4(rb[0], rb[1], rb[2], rb[3], a_h1);
        }
#pragma unroll
        for (int lim = 4; lim >= 0; lim--) {
            float t[5][4], ea[4], eb[4], f[4];
            uint32_t N70[2];
#pragma unroll
            for (int i = 0; i < 5; i++) if (i <= lim) { if (i < 4) mma_c(t[i], Q5[i], S90[0], S90[1], o[i < 4 ? i : 0][0]); else mma_zero(t[4], Q5[4], S90[0], S90[1]); }
            if (lim >= 1) { mma_zero(ea, band4, ra[0], ra[1]); mma_zero(eb, band4, ra[2], ra[3]); }
            mma_c(f, Q6s[0], S71[0], S71[1], t[0]);
#pragma unroll
            for (int i = 1; i < 5; i++) if (i <= lim) mma_c(o[i - 1][0], Q6s[i], S71[0], S71[1], t[i]);
            sts64f(mb, f[0] + e2[0][0], f[1] + e2[0][1]); sts64f(mb + 256, f[2] + e2[0][2], f[3] + e2[0][3]);
            if (lim >= 1) {
                lds64f(e2[0][0], e2[0][1], mb + 528); lds64f(e2[0][2], e2[0][3], mb + 528 + 256);
                S90[0] = pack_bf16(ea[0], ea[1]); N70[0] = pack_bf16(ea[2], ea[3]); S90[1] = pack_bf16(eb[0], eb[1]); N70[1] = pack_bf16(eb[2], eb[3]);
            }
#pragma unroll
            for (int i = 0; i < 5; i++) if (i <= lim) { if (i < 4) mma_c(t[i], Q5[i], S91[0], S91[1], o[i < 4 ? i : 0][1]); else mma_zero(t[4], Q5[4], S91[0], S91[1]); }
            if (lim >= 1) {
                mma_zero(ea, band4, rb[0], rb[1]); mma_zero(eb, band4, rb[2], rb[3]);
                mma_acc(e2[0], ra[0], ra[2], ra[1], ra[3], bE0, bE1);
            }
            mma_c(f, Q6[0], S70[0], S70[1], t[0]);
#pragma unroll
            for (int i = 1; i < 5; i++) if (i <= lim) mma_c(o[i - 1][1], Q6[i], S70[0], S70[1], t[i]);
            sts64f(mb + 64, f[0] + e2[1][0], f[1] + e2[1][1]); sts64f(mb + 320, f[2] + e2[1][2], f[3] + e2[1][3]);
            if (lim >= 1) {
                lds64f(e2[1][0], e2[1][1], mb + 528 + 64); lds64f(e2[1][2], e2[1][3], mb + 528 + 320);
                S91[0] = pack_bf16(ea[0], ea[1]); S71[0] = pack_bf16(ea[2], ea[3]); S91[1] = pack_bf16(eb[0], eb[1]); S71[1] = pack_bf16(eb[2], eb[3]);
                S70[0] = N70[0]; S70[1] = N70[1];
                mma_acc(e2[1], rb[0], rb[2], rb[1], rb[3], bE0, bE1);
            }
            if (lim >= 2) {
                a_h0 += 17 * 16; a_h1 += 17 * 16;
                ldsm4(ra[0], ra[1], ra[2], ra[3], a_h0);
                ldsm4(rb[0], rb[1], rb[2], rb[3], a_h1);
            }
            mb += 528;
        }
    }
}

__global__ void __cluster_dims__(8, 1, 1) __launch_bounds__(384, 1)
ssm_kernel(const __grid_constant__ CUtensorMap tmu, const __nv_bfloat16* __restrict__ Are, const __nv_bfloat16* __restrict__ Aim,
           const __nv_bfloat16* __restrict__ Bre, const __nv_bfloat16* __restrict__ Bim, const __nv_bfloat16* __restrict__ Cre,
           const __nv_bfloat16* __restrict__ Cim, const __nv_bfloat16* __restrict__ logdt, const __nv_bfloat16* __restrict__ Dsk,
           __nv_bfloat16* __restrict__ out) {
    extern __shared__ __align__(1024) uint8_t smem[];
    const uint32_t sm0 = (uint32_t)__cvta_generic_to_shared(smem);
    const int tid = threadIdx.x, warp = __shfl_sync(0xffffffffu, tid >> 5, 0), lane = tid & 31, g = lane >> 2, q = lane & 3, m = lane >> 3, rho = lane & 7;
    const int rank = blockIdx.x & 7, cl = blockIdx.x >> 3;
    const int chbase = 40 * cl;
    const int k = warp & 3;
    const int role = warp < 4 ? 1 : (warp < 8 ? 2 : 0);
    const int slot = role < 2 ? k : 4;
    const bool doK = role < 2 || k < 2;
    const int h = role < 2 ? role : k;
    const uint32_t chb = sm0 + OFF_CH + slot * CH_BYTES;
    const uint32_t bar0 = sm0 + OFF_BAR;
    const int ch = min(chbase + 8 * slot + rank, DCH - 1);
    TM(0);

    if (doK) {
        KParams kp;
        const size_t o = (size_t)ch * NST + 64 * h + 2 * lane;
        kp.ar = *(const uint32_t*)(Are + o); kp.ai = *(const uint32_t*)(Aim + o); kp.br = *(const uint32_t*)(Bre + o);
        kp.bi = *(const uint32_t*)(Bim + o); kp.cr = *(const uint32_t*)(Cre + o); kp.ci = *(const uint32_t*)(Cim + o);
        const uint32_t dtr = *(const unsigned short*)(logdt + ch), dskr = *(const unsigned short*)(Dsk + ch);
        if (tid == 0) {
            mbar_init(bar0, 1); mbar_init(bar0 + 8, 1); mbar_init(bar0 + 16, 1); mbar_init(bar0 + 24, 2);
            asm volatile("fence.mbarrier_init.release.cluster;" ::: "memory");
            mbar_expect(bar0, 5 * 4096); mbar_expect(bar0 + 8, 40 * 256); mbar_expect(bar0 + 16, 40 * 256);
        }
        asm volatile("barrier.cluster.arrive.relaxed.aligned;" ::: "memory");
        TM(9);
#pragma unroll
        for (int i = 0; i < 4; i++) sts128(chb + OFF_CP + (h * 128 + i * 32 + lane) * 16, 0u, 0u, 0u, 0u);
        {
            if (h == 0) sts128(chb + OFF_U4 + (lane >> 4) * U4P + (lane & 15) * 16, 0u, 0u, 0u, 0u);
            else if (lane < 16) sts128(chb + OFF_U2 + lane * 16, 0u, 0u, 0u, 0u);
        }
        const float dt = __bfloat162float(__float2bfloat16_rn(expf(bflo(dtr))));
        TM(10);
        float acc[2][3][4];
        const uint32_t sc = chb + OFF_SC0 + h * SCS;
        const float is = kgen_pass(kp, dt, sc, lane, acc);
        TM(1);
        __syncwarp();
        const float so0 = h ? 0.f : is, so1 = h ? is : 0.f;
#pragma unroll
        for (int nt = 0; nt < 3; nt++)
            sts128f(sc + nt * 512 + lane * 16, fmaf(acc[0][nt][0], so1, acc[1][nt][0] * so0), fmaf(acc[0][nt][1], so1, acc[1][nt][1] * so0),
                    fmaf(acc[0][nt][2], so1, acc[1][nt][2] * so0), fmaf(acc[0][nt][3], so1, acc[1][nt][3] * so0));
        if (tid == warp * 32 && h == 0) sts32f(bar0 + 32 + slot * 4, acc[0][2][0] * is);
        bar_sync(1 + slot, 64);
        float kf[3][4];
        const uint32_t scp = chb + OFF_SC0 + (1 - h) * SCS;
#pragma unroll
        for (int nt = 0; nt < 3; nt++) {
            float4 o = lds128f(scp + nt * 512 + lane * 16);
            kf[nt][0] = fmaf(acc[0][nt][0], so0, fmaf(acc[1][nt][0], so1, o.x)); kf[nt][1] = fmaf(acc[0][nt][1], so0, fmaf(acc[1][nt][1], so1, o.y));
            kf[nt][2] = fmaf(acc[0][nt][2], so0, fmaf(acc[1][nt][2], so1, o.z)); kf[nt][3] = fmaf(acc[0][nt][3], so0, fmaf(acc[1][nt][3], so1, o.w));
        }
        const float k512 = __uint_as_float(lds32(bar0 + 32 + slot * 4)) + __uint_as_float(lds32(sc + 1024));
        kgen_epi(chb, lane, h, kf, bflo(dskr), k512);
        TM(2);
        asm volatile("barrier.cluster.wait.acquire.aligned;" ::: "memory");
        TM(11);
    } else {
        const int li = k - 2;
        const uint32_t stg = sm0 + OFF_DS + li * 10752;
        const uint32_t ubar = bar0 + 56 + li * 32;
        if (lane == 0) {
#pragma unroll
            for (int blk = 0; blk < 4; blk++) mbar_init(ubar + blk * 8, 1);
            asm volatile("fence.mbarrier_init.release.cluster;" ::: "memory");
            asm volatile("fence.proxy.async.shared::cta;" ::: "memory");
#pragma unroll
            for (int blk = 0; blk < 4; blk++) {
                mbar_expect(ubar + blk * 8, 2560);
                tma_load4(stg + blk * 2560, &tmu, ubar + blk * 8, chbase, 0, 0, 8 * rank + 4 * li + blk);
            }
        }
        __syncwarp();
        asm volatile("barrier.cluster.arrive.relaxed.aligned;" ::: "memory");
        TM(9);
#pragma unroll
        for (int i = 0; i < 5; i++) {
            const uint32_t xz = sm0 + OFF_X + li * OFF_XS + (i * 32 + lane) * 16;
            sts128(xz, 0u, 0u, 0u, 0u); sts128(xz + RP, 0u, 0u, 0u, 0u);
        }
        asm volatile("barrier.cluster.wait.acquire.aligned;" ::: "memory");
        TM(10);
        {
            const uint32_t la = stg + (8 * m + 4 * (rho & 1) + (rho >> 1)) * 80;
            const uint32_t rb = mapa(sm0, g);
            const uint32_t da = rb + OFF_X + (rank + 2) * RP + li * 1280 + q * 16;
#pragma unroll 1
            for (int blk = 0; blk < 4; blk++) {
                mbar_wait(ubar + blk * 8);
                uint32_t r[5][4];
#pragma unroll
                for (int c5 = 0; c5 < 5; c5++) ldsm4t(r[c5][0], r[c5][1], r[c5][2], r[c5][3], la + blk * 2560 + c5 * 16);
#pragma unroll
                for (int c5 = 0; c5 < 5; c5++) st_async4(da + c5 * 256 + blk * 64, rb + OFF_BAR, r[c5][0], r[c5][1], r[c5][2], r[c5][3]);
            }
        }
        TM(11);
#pragma unroll 1
        for (int rep = 0; rep < 2; rep++) {
            if (rep) { mbar_wait(bar0); TM(1); }
            const int a = lane & 7, blk = lane >> 3;
            const uint32_t p = sm0 + OFF_X + (a + 2) * RP + li * 1280 + blk * 64;
            U5 v[5];
#pragma unroll
            for (int sl = 0; sl < 5; sl++) load_u(v[sl], p + sl * 256, blk, li, rep);
#pragma unroll
            for (int sl = 0; sl < 5; sl++) store_u(v[sl], p + sl * 256, sm0 + OFF_CH + sl * CH_BYTES, a, 4 * li + blk, rep);
        }
        __syncwarp();
        if (lane == 0) mbar_arrive(bar0 + 24);
        TM(2);
    }
    const bool isB = role == 1 || (role == 2 && k == 3);
    uint4 band2, band4; uint2 e2m;
    if (isB) {
        band_words(band2.x, band2.z, g, q, 4, 8, 0x3f80u); band_words(band2.y, band2.w, g, q, 1, 3, 0x3f80u);
        band_words(band4.x, band4.z, g, q, 0, 8, 0x3f80u); band_words(band4.y, band4.w, g, q, 1, 7, 0x3f80u);
        band_words(e2m.x, e2m.y, g, q, 7, 8, 0xffffu);
    }
    if (role == 2) bar_sync(6, 128); else bar_sync(1 + slot, 64);
    mbar_wait(bar0 + 24);
    TM(3);
    if (isB) {
        tail_terms(sm0, warp, chb, lane, band2, band4, e2m);
        __syncwarp();
        if (role == 1) bar_arrive(8 + k, 64); else bar_arrive(12, 128);
        TM(5);
    } else {
        const int p0 = role == 2 ? k : 0, p1 = role == 2 ? k + 1 : 3;
        if (p0) { build_kd(chb, lane, p0 - 1); __syncwarp(); }
        TM(4);
        const uint32_t xb = sm0 + OFF_X + slot * 256 + (m >> 1) * 64 + (m & 1) * 16 + (rho + 2) * RP;
        uint32_t ub = xb + (p0 == 0 ? OFF_XS : (2 - p0) * 32);
        uint32_t ap = chb + OFF_KP + p0 * KPS + (32 + 512 + 2 * (g - q)) * 4;
        float cur[8][4], sav[8][4];
#pragma unroll
        for (int b = 0; b < 8; b++)
#pragma unroll
            for (int c = 0; c < 4; c++) sav[b][c] = 0.f;
        uint32_t Bc[8][2], Bp[8][2];
#define BO(b) (((b) >> 2) * 1280 + ((b) & 3) * 64)
#pragma unroll
        for (int b = 0; b < 8; b += 2) ldsm4(Bp[b][0], Bp[b][1], Bp[b + 1][0], Bp[b + 1][1], ub - 2 * RP + BO(b));
        uint4 A = lda(ap);
        const uint32_t toff = (2 * q * 132 + g * 4) * 4;
#pragma unroll 1
        for (int p = p0; p < p1; p++) {
            {
                ap -= 128;
                const uint4 An = lda(ap);
#pragma unroll
                for (int b = 0; b < 8; b++) mma_c(cur[b], A, Bp[b][0], Bp[b][1], sav[b]);
                A = An;
            }
            const uint32_t un = xb + (1 - p) * 32;
#pragma unroll 1
            for (int ii = 1; ii >= 0; ii--) {
                const uint32_t cb = ub - ii * RP;
#pragma unroll
                for (int b = 0; b < 8; b += 2) ldsm4(Bc[b][0], Bc[b][1], Bc[b + 1][0], Bc[b + 1][1], cb + BO(b));
                const uint32_t nb = ii ? cb : (p < 2 ? un - 2 * RP : ub);
                const uint32_t alast = ii ? ap - 8 * 128 : ap - 7 * 128 + KPS + 16 * 128;
#pragma unroll
                for (int i0 = 7; i0 >= 0; i0--) {
                    const uint4 An = lda(i0 ? ap - (8 - i0) * 128 : alast);
#pragma unroll
                    for (int bp = 0; bp < 8; bp++) {
                        const int b = (bp - i0) & 7;
                        if (bp >= i0) mma_acc(cur[bp], A, Bc[b][0], Bc[b][1]);
                        else mma_acc(cur[bp], A, Bp[b][0], Bp[b][1]);
                    }
                    A = An;
                    if (i0 & 1) {
                        const int b = 7 - i0;
                        ldsm4(Bp[b][0], Bp[b][1], Bp[b + 1][0], Bp[b + 1][1], nb + BO(b));
                    }
                }
                ap = alast;
            }
            ub = un;
            TMP(9 + p);
            if (p == 0) {
                if (role == 0) {
#pragma unroll
                    for (int b = 0; b < 8; b++)
#pragma unroll
                        for (int c = 0; c < 4; c++) sav[b][c] = cur[b][c];
#pragma unroll 1
                    for (int sel = 0; sel < 2; sel++) build_kd(chb, lane, sel);
                    __syncwarp();
                    A = lda(ap);
                } else {
                    const uint32_t sa = sm0 + OFF_S + toff;
#pragma unroll
                    for (int j = 0; j < 4; j++)
#pragma unroll
                        for (int c = 0; c < 2; c++)
                            sts128f(sa + (c * 132 + j * 32) * 4, cur[2 * j][c], cur[2 * j][c + 2], cur[2 * j + 1][c], cur[2 * j + 1][c + 2]);
                    __syncwarp();
                    bar_arrive(12, 128);
                }
            } else {
                if (role == 2) bar_sync(12, 128); else if (p == 1) bar_sync(8 + k, 64);
                TMP(1);
                uint32_t src = chb + OFF_MB + (p - 1) * MBP * 4 + toff;
#pragma unroll 1
                for (int ns = role == 2 ? 0 : 1; ns < 2; ns++) {
#pragma unroll
                    for (int j = 0; j < 4; j++)
#pragma unroll
                        for (int c = 0; c < 2; c++) {
                            float4 v = lds128f(src + (c * 132 + j * 32) * 4);
                            cur[2 * j][c] += v.x; cur[2 * j][c + 2] += v.y; cur[2 * j + 1][c] += v.z; cur[2 * j + 1][c + 2] += v.w;
                        }
                    src = sm0 + OFF_S + toff;
                }
                const uint32_t la = OFF_DS + (8 * slot + rank) * 528 + 32 * slot + ((p - 1) * 16 + g) * 16;
#pragma unroll
                for (int c = 0; c < 2; c++) {
                    const uint32_t rb = mapa(sm0, 2 * q + c);
#pragma unroll
                    for (int bh = 0; bh < 2; bh++)
                        st_async4(rb + la + bh * 128, rb + OFF_BAR + p * 8,
                                  pack_bf16(cur[4 * bh][c], cur[4 * bh][c + 2]), pack_bf16(cur[4 * bh + 1][c], cur[4 * bh + 1][c + 2]),
                                  pack_bf16(cur[4 * bh + 2][c], cur[4 * bh + 2][c + 2]), pack_bf16(cur[4 * bh + 3][c], cur[4 * bh + 3][c + 2]));
                }
            }
        }
        TM(5);
    }
    TM(6);
#pragma unroll 1
    for (int par = 0; par < 2; par++) {
        mbar_wait(bar0 + 8 + par * 8);
        TM(7);
        const int te = 32 * (g >> 1) + (g & 1) + 16 * par + 256 * rank;
#pragma unroll 1
        for (int job = par ? 11 - warp : warp; job < 20; job += 12) {
            uint32_t r0, r1, r2, r3;
            const bool main = job < 16;
            const int c = main ? 8 * (rho >> 1) + 2 * m + (rho & 1) : 32 + 2 * m + (rho & 1);
            const int ls = par * 16 + (main ? job : 4 * (job - 16) + (rho >> 1));
            ldsm4t(r0, r1, r2, r3, sm0 + OFF_DS + c * 528 + 32 * (c >> 3) + ls * 16);
            const int pk = main ? job : 4 * (job - 16) + q;
            const int tl = 128 * (pk >> 3) + 2 * (pk & 7) + te;
            const int co = chbase + (main ? 8 * q : 32);
            if (co < DCH TMSKIP) *(uint4*)(out + (size_t)tl * DCH + co) = make_uint4(r0, r1, r2, r3);
        }
    }
    TM(8);
}

}

extern "C" void kernel_launch(void* const* d_in, const int* in_sizes, int n_in, void* d_out, int out_size) {
    typedef CUresult (*EncodeFn)(CUtensorMap*, CUtensorMapDataType, cuuint32_t, void*, const cuuint64_t*, const cuuint64_t*, const cuuint32_t*,
                                 const cuuint32_t*, CUtensorMapInterleave, CUtensorMapSwizzle, CUtensorMapL2promotion, CUtensorMapFloatOOBfill);
    static EncodeFn encode = nullptr;
    if (!encode) {
        cudaFuncSetAttribute(ssm_kernel, cudaFuncAttributeMaxDynamicSharedMemorySize, SMEM_BYTES);
        void* fn = nullptr;
        cudaDriverEntryPointQueryResult qr;
        cudaGetDriverEntryPoint("cuTensorMapEncodeTiled", &fn, cudaEnableDefault, &qr);
        encode = (EncodeFn)fn;
    }
    CUtensorMap tm;
    const cuuint64_t dims[4] = {(cuuint64_t)DCH, 4, 8, 64};
    const cuuint64_t strides[3] = {8 * DCH * 2, DCH * 2, 32 * DCH * 2};
    const cuuint32_t box[4] = {40, 4, 8, 1}, es[4] = {1, 1, 1, 1};
    encode(&tm, CU_TENSOR_MAP_DATA_TYPE_BFLOAT16, 4, d_in[0], dims, strides, box, es, CU_TENSOR_MAP_INTERLEAVE_NONE, CU_TENSOR_MAP_SWIZZLE_NONE,
           CU_TENSOR_MAP_L2_PROMOTION_L2_256B, CU_TENSOR_MAP_FLOAT_OOB_FILL_NONE);
    ssm_kernel<<<120, 384, SMEM_BYTES, cudaStreamPerThread>>>(
        tm, (const __nv_bfloat16*)d_in[1], (const __nv_bfloat16*)d_in[2], (const __nv_bfloat16*)d_in[3],
        (const __nv_bfloat16*)d_in[4], (const __nv_bfloat16*)d_in[5], (const __nv_bfloat16*)d_in[6], (const __nv_bfloat16*)d_in[7],
        (const __nv_bfloat16*)d_in[8], (__nv_bfloat16*)d_out);
}
```
